```python
import torch

def _softmax(x, axis=-1):
    return torch.softmax(x, dim=axis)
def _gelu(x):
    return torch.nn.functional.gelu(x, approximate="tanh")
def _silu(x):
    return torch.nn.functional.silu(x)
def _sigmoid(x):
    return torch.sigmoid(x)
def _layernorm(x, axis=-1, eps=1e-5):
    m = x.mean(dim=axis, keepdim=True)
    v = x.var(dim=axis, keepdim=True, unbiased=False)
    return (x - m) / torch.sqrt(v + eps)
def _scatter_add(tgt, idx, src, axis=0):
    return tgt.clone().index_add_(axis, idx, src)
def _segment_sum(src, seg, n):
    out = torch.zeros((n,) + src.shape[1:], dtype=src.dtype)
    return out.index_add_(0, seg, src)
def _pad(x, pw):
    flat = tuple(v for pair in reversed(pw) for v in pair)
    return torch.nn.functional.pad(x, flat)

kernel_name = 'recurrent_scan__mha_block_cached__dense_activation_silu__decode'

def setup_inputs():

    _w = (lambda a: (lambda t: t.to(torch.bfloat16) if t.is_floating_point() else t)(torch.as_tensor(a)))
    def _A_setup():
        B, Sq, D = 4, 1, 512
        H, Sk, Dh = 32, 8192, 128
        return {
            "x": _w((lambda *s: torch.randn(*s, dtype=torch.bfloat16) * 0.4)(B, Sq, D)),
            "k_cache": _w((lambda *s: torch.randn(*s, dtype=torch.bfloat16) * 1.6)(B, H, Sk, Dh)),
            "v_cache": _w((lambda *s: torch.randn(*s, dtype=torch.bfloat16) * 1.6)(B, H, Sk, Dh)),
            "wq": _w((lambda *s: torch.randn(*s, dtype=torch.bfloat16) * 1.6)(D, H * Dh) * (D ** -0.5)),
            "wo": _w((lambda *s: torch.randn(*s, dtype=torch.bfloat16) * 1.6)(H * Dh, D) * ((H * Dh) ** -0.5)),
        }
    _A_in = _A_setup()

    def _B_setup():
        B, S, D, F = 4, 1, 512, 1376
        return {
            "x": _w((lambda *s: torch.randn(*s, dtype=torch.bfloat16) * 0.4)(B, S, D)),
            "w1": _w((lambda *s: torch.randn(*s, dtype=torch.bfloat16) * 1.6)(D, F) * (D ** -0.5)),
            "w2": _w((lambda *s: torch.randn(*s, dtype=torch.bfloat16) * 1.6)(F, D) * (F ** -0.5)),
        }
    _B_in = _B_setup()

    return {
        "A_x": _A_in["x"],
        "A_k_cache": _A_in["k_cache"],
        "A_v_cache": _A_in["v_cache"],
        "A_wq": _A_in["wq"],
        "A_wo": _A_in["wo"],
        "B_x": _B_in["x"],
        "B_w1": _B_in["w1"],
        "B_w2": _B_in["w2"],
    }

def reference(A_x, A_k_cache, A_v_cache, A_wq, A_wo, B_x, B_w1, B_w2):
    def _A_ref(x, k_cache, v_cache, wq, wo):
        B, Sq, D = x.shape
        H, Dh = 32, 128
        q = (lambda x, *d: x.permute(*d))((x @ wq).reshape(B, Sq, H, Dh), 0, 2, 1, 3)
        scores = torch.einsum("bhqd,bhkd->bhqk", q, k_cache) * (Dh ** -0.5)
        p = _softmax(scores, axis=-1)
        o = torch.einsum("bhqk,bhkd->bhqd", p, v_cache)
        return (lambda x, *d: x.permute(*d))(o, 0, 2, 1, 3).reshape(B, Sq, H * Dh) @ wo

    def _B_ref(x, w1, w2):
        h = torch.einsum("bsd,df->bsf", x, w1)
        h = _silu(h)
        out = torch.einsum("bsf,fd->bsd", h, w2)
        return out

    x = A_x
    xn = _layernorm(x, axis=-1)
    s = _A_ref(xn, A_k_cache, A_v_cache, A_wq, A_wo)
    g = _silu(_B_ref(xn, B_w1, B_w2))
    return x + s * g
```

```cpp
#include <cuda_runtime.h>
#include <cuda_bf16.h>
#include <stdint.h>

namespace fk {

#define FK_NST 4
#define FK_EVICT_FIRST 1

constexpr int NB = 4, NH = 32, SK = 8192, DH = 128, DM = 512, FF = 1376;
constexpr int TK = 128;
constexpr int NT = SK / TK;
constexpr int STAGE_BYTES = TK * DH * 2;
constexpr int NST = FK_NST;
constexpr int NCW = 8;
constexpr int NTHREADS = NCW * 32;
constexpr int N_ATT = NB * NH;
constexpr int N_FFN = 4;
constexpr int FS = FF / N_FFN;
constexpr int N_CTA = N_ATT + N_FFN;

#define FK_FIRST 2
#define FK_PRE 1
#define FK_PACE 1
#define FK_WO_TOUCH 1
#define FK_INIT_WR 1
#define FK_THROTTLE 1
#define FK_LEAD 0
#define FK_NJ 8
#define FK_POLLSLEEP 0
#define FK_WTILE 3

constexpr int W_POS = 2 * FK_WTILE;
constexpr int NSEQ = 2 * NT + 4;

constexpr int OFF_BAR = NST * STAGE_BYTES;
constexpr int OFF_XN  = OFF_BAR + 256;
constexpr int OFF_RED = OFF_XN + 8192;
constexpr int OFF_Q   = OFF_RED + 4096;
constexpr int OFF_X   = OFF_Q + 256;
constexpr int OFF_ML  = OFF_X + 4096;
constexpr int OFF_OH  = OFF_ML + 64;
constexpr int SMEM_ATT = OFF_OH + 256;
constexpr int FFN_CHUNK = 64 * FS * 2;
constexpr int NBF = (NST >= 6) ? 4 : (NST == 5 ? 2 : 2);
constexpr int FFN_XN = NBF * FFN_CHUNK, FFN_H = FFN_XN + 8192, FFN_RED = FFN_H + 5504, FFN_BAR = FFN_RED + 32768;
constexpr int SMEM_FFN = FFN_BAR + 64;
static_assert(FFN_CHUNK == 43 * DM * 2, "chunk geometry");
constexpr int SMEM_BYTES = SMEM_ATT > SMEM_FFN ? SMEM_ATT : SMEM_FFN;

__device__ uint4 g_q_part[NH * NB * 32];
__device__ uint4 g_attn_part[NB * 32 * 2 * NH * 8];
__device__ uint4 g_ffn_part[NB * 32 * N_FFN * 8];
#define FK_ONE4 1u, 1u, 1u, 1u
#define FK_ONE16 FK_ONE4, FK_ONE4, FK_ONE4, FK_ONE4
#define FK_ONE64 FK_ONE16, FK_ONE16, FK_ONE16, FK_ONE16
__device__ uint32_t g_progress;
__device__ uint32_t g_epoch[N_CTA] = {FK_ONE64, FK_ONE64, FK_ONE4};

__device__ unsigned long long g_tile_times[N_ATT * 64];
#define FK_STAMP(i) do {} while (0)

__device__ __forceinline__ uint32_t smem_u32(const void* p) { return (uint32_t)__cvta_generic_to_shared(p); }

__device__ __forceinline__ void mbar_init(uint32_t bar, uint32_t cnt) {
    asm volatile("mbarrier.init.shared::cta.b64 [%0], %1;" :: "r"(bar), "r"(cnt) : "memory");
}
__device__ __forceinline__ void mbar_expect_tx(uint32_t bar, uint32_t bytes) {
    asm volatile("mbarrier.arrive.expect_tx.shared::cta.b64 _, [%0], %1;" :: "r"(bar), "r"(bytes) : "memory");
}
__device__ __forceinline__ uint32_t atom_inc_shared(uint32_t addr) {
    uint32_t old;
    asm volatile("atom.relaxed.cta.shared::cta.add.u32 %0, [%1], 1;" : "=r"(old) : "r"(addr) : "memory");
    return old;
}
__device__ __forceinline__ void mbar_wait(uint32_t bar, uint32_t parity) {
    asm volatile(
        "{\n"
        ".reg .pred p;\n"
        "FK_WAIT:\n"
        "mbarrier.try_wait.parity.shared::cta.b64 p, [%0], %1;\n"
        "@p bra FK_DONE;\n"
        "bra FK_WAIT;\n"
        "FK_DONE:\n"
        "}\n" :: "r"(bar), "r"(parity) : "memory");
}
__device__ __forceinline__ void bulk_load(uint32_t dst, const void* src, uint32_t bytes, uint32_t bar, uint64_t pol) {
    asm volatile("cp.async.bulk.shared::cluster.global.mbarrier::complete_tx::bytes.L2::cache_hint [%0], [%1], %2, [%3], %4;"
                 :: "r"(dst), "l"(src), "r"(bytes), "r"(bar), "l"(pol) : "memory");
}
__device__ __forceinline__ uint4 ldg_nc(const void* p) {
    uint4 v;
    asm volatile("ld.global.nc.L1::no_allocate.v4.u32 {%0,%1,%2,%3}, [%4];"
                 : "=r"(v.x), "=r"(v.y), "=r"(v.z), "=r"(v.w) : "l"(p));
    return v;
}
__device__ __forceinline__ void bulk_load_plain(uint32_t dst, const void* src, uint32_t bytes, uint32_t bar) {
    asm volatile("cp.async.bulk.shared::cluster.global.mbarrier::complete_tx::bytes [%0], [%1], %2, [%3];"
                 :: "r"(dst), "l"(src), "r"(bytes), "r"(bar) : "memory");
}
__device__ __forceinline__ uint32_t ldg_nc32(const void* p) {
    uint32_t v;
    asm volatile("ld.global.nc.L1::no_allocate.u32 %0, [%1];" : "=r"(v) : "l"(p));
    return v;
}
__device__ __forceinline__ uint32_t ld_volatile32(const uint32_t* p) {
    uint32_t v;
    asm volatile("ld.relaxed.gpu.global.u32 %0, [%1];" : "=r"(v) : "l"(p) : "memory");
    return v;
}
__device__ __forceinline__ bool mbar_test(uint32_t bar, uint32_t parity) {
    uint32_t ok;
    asm volatile("{\n.reg .pred p;\nmbarrier.test_wait.parity.shared::cta.b64 p, [%1], %2;\nselp.u32 %0, 1, 0, p;\n}\n"
                 : "=r"(ok) : "r"(bar), "r"(parity) : "memory");
    return ok != 0;
}
__device__ __forceinline__ uint4 ld_relaxed(const uint4* p) {
    uint4 v;
    asm volatile("ld.relaxed.gpu.global.v4.u32 {%0,%1,%2,%3}, [%4];"
                 : "=r"(v.x), "=r"(v.y), "=r"(v.z), "=r"(v.w) : "l"(p) : "memory");
    return v;
}
__device__ __forceinline__ void st_relaxed(uint4* p, uint4 v) {
    asm volatile("st.relaxed.gpu.global.v4.u32 [%0], {%1,%2,%3,%4};"
                 :: "l"(p), "r"(v.x), "r"(v.y), "r"(v.z), "r"(v.w) : "memory");
}
__device__ __forceinline__ void ldsm_x4(uint32_t (&r)[4], uint32_t addr) {
    asm volatile("ldmatrix.sync.aligned.m8n8.x4.shared.b16 {%0,%1,%2,%3}, [%4];"
                 : "=r"(r[0]), "=r"(r[1]), "=r"(r[2]), "=r"(r[3]) : "r"(addr) : "memory");
}
__device__ __forceinline__ void ldsm_x4_t(uint32_t (&r)[4], uint32_t addr) {
    asm volatile("ldmatrix.sync.aligned.m8n8.x4.trans.shared.b16 {%0,%1,%2,%3}, [%4];"
                 : "=r"(r[0]), "=r"(r[1]), "=r"(r[2]), "=r"(r[3]) : "r"(addr) : "memory");
}
__device__ __forceinline__ void mma_bf16(float (&c)[4], const uint32_t (&a)[4], uint32_t b0, uint32_t b1) {
    asm volatile("mma.sync.aligned.m16n8k16.row.col.f32.bf16.bf16.f32 {%0,%1,%2,%3}, {%4,%5,%6,%7}, {%8,%9}, {%0,%1,%2,%3};"
                 : "+f"(c[0]), "+f"(c[1]), "+f"(c[2]), "+f"(c[3])
                 : "r"(a[0]), "r"(a[1]), "r"(a[2]), "r"(a[3]), "r"(b0), "r"(b1));
}
__device__ __forceinline__ uint32_t prmt(uint32_t a, uint32_t b, uint32_t sel) {
    uint32_t r;
    asm volatile("prmt.b32 %0, %1, %2, %3;" : "=r"(r) : "r"(a), "r"(b), "r"(sel));
    return r;
}
__device__ __forceinline__ float ex2(float x) {
    float r;
    asm("ex2.approx.ftz.f32 %0, %1;" : "=f"(r) : "f"(x));
    return r;
}
__device__ __forceinline__ uint32_t pack_bf16(float lo, float hi) {
    uint32_t r;
    asm("cvt.rn.bf16x2.f32 %0, %1, %2;" : "=r"(r) : "f"(hi), "f"(lo));
    return r;
}
__device__ __forceinline__ float bf_lo(uint32_t w) { return __uint_as_float(w << 16); }
__device__ __forceinline__ float bf_hi(uint32_t w) { return __uint_as_float(w & 0xffff0000u); }
__device__ __forceinline__ float bf16r(float x) { return __bfloat162float(__float2bfloat16_rn(x)); }
__device__ __forceinline__ float silu_f(float x) { return x / (1.0f + __expf(-x)); }

__device__ __forceinline__ void warp_layernorm(const uint4 a, const uint4 b, float (&xn)[16]) {
    float v[16];
    v[0] = bf_lo(a.x); v[1] = bf_hi(a.x); v[2] = bf_lo(a.y); v[3] = bf_hi(a.y);
    v[4] = bf_lo(a.z); v[5] = bf_hi(a.z); v[6] = bf_lo(a.w); v[7] = bf_hi(a.w);
    v[8] = bf_lo(b.x); v[9] = bf_hi(b.x); v[10] = bf_lo(b.y); v[11] = bf_hi(b.y);
    v[12] = bf_lo(b.z); v[13] = bf_hi(b.z); v[14] = bf_lo(b.w); v[15] = bf_hi(b.w);
    float s = 0.f;
#pragma unroll
    for (int i = 0; i < 16; i++) s += v[i];
#pragma unroll
    for (int o = 16; o; o >>= 1) s += __shfl_xor_sync(0xffffffffu, s, o);
    const float mean = s * (1.0f / DM);
    float ss = 0.f;
#pragma unroll
    for (int i = 0; i < 16; i++) { const float d = v[i] - mean; ss = fmaf(d, d, ss); }
#pragma unroll
    for (int o = 16; o; o >>= 1) ss += __shfl_xor_sync(0xffffffffu, ss, o);
    const float m_bf = bf16r(mean);
    const float den = bf16r(sqrtf(bf16r(bf16r(ss * (1.0f / DM)) + 1e-5f)));
#pragma unroll
    for (int i = 0; i < 16; i++) xn[i] = bf16r(__fdiv_rn(bf16r(v[i] - m_bf), den));
}

__device__ __forceinline__ bool ll_valid(const uint4& v, uint32_t tag) { return v.y == tag && v.w == tag; }

__device__ __forceinline__ void ffn_cta(uint8_t* smem, int f, uint32_t tag,
                                        const __nv_bfloat16* __restrict__ x,
                                        const __nv_bfloat16* __restrict__ w1,
                                        const __nv_bfloat16* __restrict__ w2) {
    const int tid = threadIdx.x, warp = tid >> 5, lane = tid & 31;
    const uint32_t sbase = smem_u32(smem), bar = sbase + FFN_BAR;
    float* xnT = reinterpret_cast<float*>(smem + FFN_XN);
    float* hT  = reinterpret_cast<float*>(smem + FFN_H);
    float* red = reinterpret_cast<float*>(smem + FFN_RED);
    if (tid == 0) {
#pragma unroll
        for (int s = 0; s < NBF; s++) mbar_init(bar + s * 8, 1);
    }
    __syncthreads();
    auto issue = [&](int c) {
        const int s = c % NBF;
        if (tid == 0) mbar_expect_tx(bar + s * 8, FFN_CHUNK);
        if (c < 8) {
            __syncthreads();
            if (tid < 64) bulk_load_plain(sbase + s * FFN_CHUNK + tid * (FS * 2), w1 + (size_t)(c * 64 + tid) * FF + f * FS, FS * 2, bar + s * 8);
        } else if (tid == 0) {
            bulk_load_plain(sbase + s * FFN_CHUNK, w2 + (size_t)(f * FS + (c - 8) * 43) * DM, FFN_CHUNK, bar + s * 8);
        }
    };
    for (int c = 0; c < NBF; c++) issue(c);
    if (warp < NB) {
        float xn[16];
        const uint4 xa = ldg_nc(x + warp * DM + lane * 16), xb = ldg_nc(x + warp * DM + lane * 16 + 8);
        warp_layernorm(xa, xb, xn);
#pragma unroll
        for (int i = 0; i < 16; i++) xnT[(lane * 16 + i) * 4 + warp] = xn[i];
    }
    __syncthreads();
    float acc[4][8];
#pragma unroll
    for (int b = 0; b < 4; b++)
#pragma unroll
        for (int c = 0; c < 8; c++) acc[b][c] = 0.f;
#pragma unroll 1
    for (int c = 0; c < 16; c++) {
        const int s = c % NBF;
        mbar_wait(bar + s * 8, (c / NBF) & 1);
        const bool st1 = c < 8;
        const int cg = st1 ? tid % 43 : (tid & 63), r0 = st1 ? tid / 43 : (tid >> 6);
        const int rstep = st1 ? 5 : 4, nrows = st1 ? 64 : 43, rbytes = st1 ? FS * 2 : DM * 2;
        const float* vec = st1 ? xnT + c * 64 * 4 : hT + (c - 8) * 43 * 4;
        const uint8_t* wb = smem + s * FFN_CHUNK + cg * 16;
        if (!st1 || tid < 43 * 5) {
#pragma unroll 2
            for (int k = r0; k < nrows; k += rstep) {
                const uint4 w = *reinterpret_cast<const uint4*>(wb + k * rbytes);
                const float4 xv = *reinterpret_cast<const float4*>(vec + k * 4);
                const float wf[8] = {bf_lo(w.x), bf_hi(w.x), bf_lo(w.y), bf_hi(w.y), bf_lo(w.z), bf_hi(w.z), bf_lo(w.w), bf_hi(w.w)};
#pragma unroll
                for (int j = 0; j < 8; j++) {
                    acc[0][j] = fmaf(xv.x, wf[j], acc[0][j]);
                    acc[1][j] = fmaf(xv.y, wf[j], acc[1][j]);
                    acc[2][j] = fmaf(xv.z, wf[j], acc[2][j]);
                    acc[3][j] = fmaf(xv.w, wf[j], acc[3][j]);
                }
            }
        }
        __syncthreads();
        if (c + NBF < 16) issue(c + NBF);
        if (c == 7) {
            if (tid < 43 * 5) {
#pragma unroll
                for (int b = 0; b < 4; b++)
#pragma unroll
                    for (int j = 0; j < 8; j++) red[(r0 * 4 + b) * FS + cg * 8 + j] = acc[b][j];
            }
#pragma unroll
            for (int b = 0; b < 4; b++)
#pragma unroll
                for (int j = 0; j < 8; j++) acc[b][j] = 0.f;
            __syncthreads();
            for (int i = tid; i < 4 * FS; i += NTHREADS) {
                const int b = i / FS, cc = i % FS;
                float sum = 0.f;
#pragma unroll
                for (int ks = 0; ks < 5; ks++) sum += red[(ks * 4 + b) * FS + cc];
                hT[cc * 4 + b] = bf16r(silu_f(bf16r(sum)));
            }
            __syncthreads();
        }
    }
    {
        const int cg = tid & 63, fs = tid >> 6;
#pragma unroll
        for (int b = 0; b < 4; b++)
#pragma unroll
            for (int j = 0; j < 8; j++) red[(fs * 4 + b) * DM + cg * 8 + j] = acc[b][j];
    }
    __syncthreads();
    for (int i = tid; i < NB * 256; i += NTHREADS) {
        const int b = i >> 8, j = (i >> 3) & 31, p = i & 7;
        float s0 = 0.f, s1 = 0.f;
#pragma unroll
        for (int fs = 0; fs < 4; fs++) { s0 += red[(fs * 4 + b) * DM + 16 * j + p]; s1 += red[(fs * 4 + b) * DM + 16 * j + 8 + p]; }
        st_relaxed(&g_ffn_part[((b * 32 + j) * N_FFN + f) * 8 + p],
                   make_uint4(__float_as_uint(s0), tag, __float_as_uint(s1), tag));
    }
}

__global__ void __launch_bounds__(NTHREADS, 1)
fused_decode_kernel(const __nv_bfloat16* __restrict__ x, const __nv_bfloat16* __restrict__ Kc,
                    const __nv_bfloat16* __restrict__ Vc, const __nv_bfloat16* __restrict__ wq,
                    const __nv_bfloat16* __restrict__ wo, const __nv_bfloat16* __restrict__ w1,
                    const __nv_bfloat16* __restrict__ w2, __nv_bfloat16* __restrict__ out) {
    extern __shared__ __align__(1024) uint8_t smem[];
    const int cta = blockIdx.x;
    const int tid = threadIdx.x, warp = tid >> 5, lane = tid & 31;
    if (tid == 0) FK_STAMP(5);
    if (cta >= N_ATT) {
        const uint32_t tag = ld_volatile32(&g_epoch[cta]);
        ffn_cta(smem, cta - N_ATT, tag, x, w1, w2);
        if (tid == 0) { g_epoch[cta] = tag + 1; FK_STAMP(4); }
        return;
    }

    const int b = cta & 3, h = cta >> 2;
    const int bh = b * NH + h;
    const uint32_t sbase = smem_u32(smem);
    const uint32_t bar_full = sbase + OFF_BAR;
    const uint32_t cnt_rel = bar_full + NST * 8;
    const char* kp = reinterpret_cast<const char*>(Kc) + (size_t)bh * SK * DH * 2;
    const char* vp = reinterpret_cast<const char*>(Vc) + (size_t)bh * SK * DH * 2;
    const char* wop = reinterpret_cast<const char*>(wo) + (size_t)h * DH * DM * 2;
    uint64_t pol = 0;
    asm volatile("createpolicy.fractional.L2::evict_first.b64 %0, 1.0;" : "=l"(pol));
    auto issue_load = [&](int q, int s) {
        mbar_expect_tx(bar_full + s * 8, STAGE_BYTES);
        if (q >= W_POS && q < W_POS + 4) {
            bulk_load_plain(sbase + s * STAGE_BYTES, wop + (size_t)(q - W_POS) * STAGE_BYTES, STAGE_BYTES, bar_full + s * 8);
        } else {
            const int r = q < W_POS ? q : q - 4;
            bulk_load(sbase + s * STAGE_BYTES, ((r & 1) ? vp : kp) + (size_t)(r >> 1) * STAGE_BYTES, STAGE_BYTES, bar_full + s * 8, pol);
        }
    };

    const int g = lane >> 2, t = lane & 3;
    float* xn_s  = reinterpret_cast<float*>(smem + OFF_XN);
    float* red_s = reinterpret_cast<float*>(smem + OFF_RED);
    __nv_bfloat16* q_s = reinterpret_cast<__nv_bfloat16*>(smem + OFF_Q);
    float* ml_s = reinterpret_cast<float*>(smem + OFF_ML);
    __nv_bfloat16* o_s = reinterpret_cast<__nv_bfloat16*>(smem + OFF_OH);

    uint4* const q_out = &g_q_part[(h * NB + (lane >> 3)) * 32 + b * 8 + (lane & 7)];
    uint4* const a_out = &g_attn_part[((b * 32 + (warp & 3) * 8 + t) * (2 * NH) + h * 2 + (warp >> 2)) * 8 + g];

    volatile uint32_t* q_flag = reinterpret_cast<volatile uint32_t*>(smem + OFF_BAR + 192);
    const uint32_t bar_x = bar_full + 200;
    if (tid == 0) {
#pragma unroll
        for (int s = 0; s < NST; s++) {
            mbar_init(bar_full + s * 8, 1);
            *reinterpret_cast<volatile uint32_t*>(smem + OFF_BAR + NST * 8 + s * 4) = 0;
        }
        mbar_init(bar_x, 1);
        *q_flag = 0;
        mbar_expect_tx(bar_x, NB * DM * 2);
        bulk_load_plain(sbase + OFF_X, x, NB * DM * 2, bar_x);
#pragma unroll 1
        for (int s = 0; s < FK_PRE; s++) issue_load(s, s);
    }
    uint32_t qf[8][2];
    uint32_t tag;
    {
        uint32_t w[32];
        const __nv_bfloat16* wp = wq + (size_t)(warp * 64 + (lane >> 4) * 32) * (NH * DH) + h * DH + b * 32 + (lane & 15) * 2;
#pragma unroll
        for (int i = 0; i < 32; i++) w[i] = ldg_nc32(wp + (size_t)i * (NH * DH));
        tag = ld_volatile32(&g_epoch[cta]);
        if (tid == 0) {
#pragma unroll 1
            for (int s = FK_PRE; s < FK_FIRST; s++) issue_load(s, s);
            asm volatile("prefetch.global.L2 [%0];" :: "l"(wop));
            FK_STAMP(0);
        }
        if (warp == 0) st_relaxed(q_out, make_uint4(0, 0, 0, 0));
        st_relaxed(a_out, make_uint4(0, 0, 0, 0));
        st_relaxed(a_out + 4 * (2 * NH) * 8, make_uint4(0, 0, 0, 0));
        __syncthreads();
        if (warp < 4) {
            float xn[16];
            mbar_wait(bar_x, 0);
            if (tid == 0) FK_STAMP(14);
            const uint4 xa = *reinterpret_cast<const uint4*>(smem + OFF_X + warp * DM * 2 + lane * 32);
            const uint4 xb = *reinterpret_cast<const uint4*>(smem + OFF_X + warp * DM * 2 + lane * 32 + 16);
            warp_layernorm(xa, xb, xn);
#pragma unroll
            for (int i = 0; i < 16; i += 4)
                *reinterpret_cast<float4*>(xn_s + warp * DM + lane * 16 + i) = make_float4(xn[i], xn[i + 1], xn[i + 2], xn[i + 3]);
        }
        if (tid == 0) FK_STAMP(6);
        __syncthreads();
        if (tid == 0) FK_STAMP(7);
        float acc[4][2];
#pragma unroll
        for (int bb = 0; bb < 4; bb++) acc[bb][0] = acc[bb][1] = 0.f;
        const float* xp = xn_s + warp * 64 + (lane >> 4) * 32;
#pragma unroll
        for (int i4 = 0; i4 < 8; i4++) {
#pragma unroll
            for (int bb = 0; bb < 4; bb++) {
                const float4 xv = *reinterpret_cast<const float4*>(xp + bb * DM + i4 * 4);
                const float xs[4] = {xv.x, xv.y, xv.z, xv.w};
#pragma unroll
                for (int u = 0; u < 4; u++) {
                    acc[bb][0] = fmaf(xs[u], bf_lo(w[i4 * 4 + u]), acc[bb][0]);
                    acc[bb][1] = fmaf(xs[u], bf_hi(w[i4 * 4 + u]), acc[bb][1]);
                }
            }
        }
        const bool up = lane >= 16;
        float k0 = up ? acc[2][0] : acc[0][0], k1 = up ? acc[2][1] : acc[0][1];
        float k2 = up ? acc[3][0] : acc[1][0], k3 = up ? acc[3][1] : acc[1][1];
        k0 += __shfl_xor_sync(0xffffffffu, up ? acc[0][0] : acc[2][0], 16);
        k1 += __shfl_xor_sync(0xffffffffu, up ? acc[0][1] : acc[2][1], 16);
        k2 += __shfl_xor_sync(0xffffffffu, up ? acc[1][0] : acc[3][0], 16);
        k3 += __shfl_xor_sync(0xffffffffu, up ? acc[1][1] : acc[3][1], 16);
        float* rp = red_s + warp * 128 + (up ? 64 : 0) + (lane & 15) * 2;
        *reinterpret_cast<float2*>(rp)      = make_float2(k0, k1);
        *reinterpret_cast<float2*>(rp + 32) = make_float2(k2, k3);
        if (tid == 0) FK_STAMP(8);
        __syncthreads();
        if (tid == 0) FK_STAMP(9);
        if (warp == 0) {
            float4 s = make_float4(0.f, 0.f, 0.f, 0.f);
#pragma unroll
            for (int w8 = 0; w8 < NCW; w8++) {
                const float4 v = *reinterpret_cast<const float4*>(red_s + w8 * 128 + lane * 4);
                s.x += v.x; s.y += v.y; s.z += v.z; s.w += v.w;
            }
            st_relaxed(q_out, make_uint4(pack_bf16(s.x, s.y), tag, pack_bf16(s.z, s.w), tag));
            const uint4* p = &g_q_part[(h * NB + b) * 32 + lane];
            uint4 v = ld_relaxed(p);
            for (int spin = 0; !ll_valid(v, tag) && spin < (1 << 20); spin++) v = ld_relaxed(p);
            *reinterpret_cast<uint2*>(q_s + lane * 4) = make_uint2(v.x, v.z);
            if (lane == 0) *q_flag = 1;
            if (tid == 0) FK_STAMP(10);
        }
        if (tid == NTHREADS - 32) {
            int next = FK_FIRST, watch = 0;
            while (next < NST) {
                if (mbar_test(bar_full + watch * 8, 0)) { issue_load(next, next); next++; watch++; }
                else if (*q_flag) break;
            }
#pragma unroll 1
            for (; next < NST; next++) issue_load(next, next);
            FK_STAMP(13);
        }
        __syncwarp();
        __syncthreads();
#pragma unroll
        for (int j = 0; j < 8; j++) {
            const int c = (j ^ g) & 7;
            qf[j][0] = *reinterpret_cast<const uint32_t*>(q_s + c * 8 + 2 * t);
            qf[j][1] = *reinterpret_cast<const uint32_t*>(q_s + 64 + c * 8 + 2 * t);
        }
    }
    if (tid == 0) FK_STAMP(1);

    constexpr float SC = 0.08838834764831845f * 1.4426950408889634f;
    const int li = lane & 7, lm = lane >> 3;
    const uint32_t k_off = (uint32_t)((warp * 16 + li + 8 * (lm & 1)) * 256 + (lm >> 1) * 128 + li * 16);
    const uint32_t v_off = (uint32_t)((warp * 16 + li + 8 * (lm >> 1)) * 256 + (lm & 1) * 128 + li * 16);
    const bool diag = (t == (g >> 1));
    const int rsel = g ^ (2 * t);
    const uint32_t ones[4] = {0x3f803f80u, 0x3f803f80u, 0x3f803f80u, 0x3f803f80u};

    float acc0[4] = {0.f, 0.f, 0.f, 0.f}, acc1[4] = {0.f, 0.f, 0.f, 0.f}, lacc[4] = {0.f, 0.f, 0.f, 0.f};
    float m_run = -INFINITY;
    int st = 0; uint32_t ph = 0;
    int seq = NST;
    uint32_t wa[4][8][4];
    float g0 = 0.f, g1 = 0.f, x0 = 0.f, x1 = 0.f;
    uint4 gv = make_uint4(0, 0, 0, 0);
    const uint32_t prog_base = (tag - 1) * (uint32_t)(N_ATT * NT);
    volatile uint32_t* prog_s = reinterpret_cast<volatile uint32_t*>(smem + OFF_BAR + 208);
    uint32_t prog_v = prog_base;
    if (tid == 0) *prog_s = prog_base;
    __syncthreads();
    const int cp = lane & 7, q4 = lane >> 3;

#pragma unroll 1
    for (int it = 0; it < NT; it++) {
        if (it == FK_WTILE) {
            if (tid == 0) FK_STAMP(12);
#pragma unroll
            for (int q = 0; q < 4; q++) {
                mbar_wait(bar_full + st * 8, ph);
                if ((q >> 1) == (warp >> 2)) {
                    const uint32_t wb = sbase + st * STAGE_BYTES + (li + 8 * (lm >> 1)) * 1024 + (warp & 3) * 256 + (lm & 1) * 128 + li * 16;
#pragma unroll
                    for (int j = 0; j < 8; j++) { ldsm_x4_t(wa[(q & 1) * 2][j], wb ^ (j << 4)); ldsm_x4_t(wa[(q & 1) * 2 + 1][j], (wb + 16384) ^ (j << 4)); }
                }
                if (lane == 0) {
                    const uint32_t rel = atom_inc_shared(cnt_rel + st * 4);
                    if ((rel & (NCW - 1)) == NCW - 1) issue_load(seq, st);
                }
                __syncwarp();
                seq++;
                if (++st == NST) { st = 0; ph ^= 1; }
            }
            if (tid == 0) FK_STAMP(11);
        }
        if (it == NT - 12 && warp == 0) {
            gv = ld_relaxed(&g_ffn_part[((b * 32 + h) * N_FFN + q4) * 8 + cp]);
        }
        if (it == NT - 2 && warp == 0) {
            x0 = __bfloat162float(reinterpret_cast<const __nv_bfloat16*>(smem + OFF_X)[b * DM + h * 16 + cp]);
            x1 = __bfloat162float(reinterpret_cast<const __nv_bfloat16*>(smem + OFF_X)[b * DM + h * 16 + 8 + cp]);
            const uint4* p = &g_ffn_part[((b * 32 + h) * N_FFN + q4) * 8 + cp];
            uint4 v = gv;
            for (int spin = 0; !ll_valid(v, tag) && spin < (1 << 20); spin++) { __nanosleep(64); v = ld_relaxed(p); }
            __syncwarp();
            g0 = __uint_as_float(v.x); g1 = __uint_as_float(v.z);
            g0 += __shfl_xor_sync(0xffffffffu, g0, 8);  g1 += __shfl_xor_sync(0xffffffffu, g1, 8);
            g0 += __shfl_xor_sync(0xffffffffu, g0, 16); g1 += __shfl_xor_sync(0xffffffffu, g1, 16);
            g0 = bf16r(silu_f(bf16r(g0))); g1 = bf16r(silu_f(bf16r(g1)));
        }
        if (tid == 0) {
            *prog_s = prog_v;
            prog_v = ld_volatile32(&g_progress);
        }
        mbar_wait(bar_full + st * 8, ph);
        float c0[4] = {0.f, 0.f, 0.f, 0.f}, c1[4] = {0.f, 0.f, 0.f, 0.f};
        const uint32_t kb = sbase + st * STAGE_BYTES + k_off;
#pragma unroll
        for (int j = 0; j < FK_NJ; j++) {
            uint32_t a[4];
            ldsm_x4(a, kb ^ (j << 4));
            mma_bf16((j & 1) ? c1 : c0, a, qf[j][0], qf[j][1]);
        }
        uint32_t relK = 0;
        if (seq < NSEQ && lane == 0) relK = atom_inc_shared(cnt_rel + st * 4);
        float s0 = (g & 1) ? (c0[1] + c1[1]) : (c0[0] + c1[0]);
        float s1 = (g & 1) ? (c0[3] + c1[3]) : (c0[2] + c1[2]);
        s0 = diag ? s0 : -INFINITY;
        s1 = diag ? s1 : -INFINITY;
        int key = __float_as_int(fmaxf(s0, s1));
        key ^= (key >> 31) & 0x7fffffff;
        key = __reduce_max_sync(0xffffffffu, key);
        key ^= (key >> 31) & 0x7fffffff;
        const float tmax = __int_as_float(key);
        if (tmax > m_run) {
            const float sc = ex2((m_run - tmax) * SC);
#pragma unroll
            for (int i = 0; i < 4; i++) { acc0[i] *= sc; acc1[i] *= sc; }
            lacc[0] *= sc;
            m_run = tmax;
        }
        const float mc = -m_run * SC;
        const uint32_t pk = pack_bf16(ex2(fmaf(s0, SC, mc)), ex2(fmaf(s1, SC, mc)));
        const uint32_t xx = __shfl_sync(0xffffffffu, pk, 9 * t), yy = __shfl_sync(0xffffffffu, pk, 9 * t + 4);
        const uint32_t pp0 = __byte_perm(xx, yy, 0x5410), pp1 = __byte_perm(xx, yy, 0x7632);
        if ((relK & (NCW - 1)) == NCW - 1) {
            const uint32_t lim = prog_base + (uint32_t)(it * N_ATT - (FK_LEAD));
            uint32_t pv = *prog_s;
            for (int spin = 0; (int)(pv - lim) < 0 && spin < 4096; spin++) pv = ld_volatile32(&g_progress);
            issue_load(seq, st);
        }
        seq++;
        if (++st == NST) { st = 0; ph ^= 1; }
        mbar_wait(bar_full + st * 8, ph);
        const uint32_t vb = sbase + st * STAGE_BYTES + v_off;
#pragma unroll
        for (int j = 0; j < FK_NJ; j++) {
            uint32_t a[4];
            ldsm_x4_t(a, vb ^ (j << 4));
            const uint32_t msk = (j == rsel ? 0x0000ffffu : 0u) | (j == (rsel ^ 1) ? 0xffff0000u : 0u);
            mma_bf16((j & 1) ? acc1 : acc0, a, pp0 & msk, pp1 & msk);
        }
        uint32_t relV = 0;
        if (seq < NSEQ && lane == 0) relV = atom_inc_shared(cnt_rel + st * 4);
        mma_bf16(lacc, ones, pp0, pp1);
        if ((relV & (NCW - 1)) == NCW - 1) issue_load(seq, st);
        if (tid == NTHREADS - 32) asm volatile("red.relaxed.gpu.global.add.u32 [%0], 1;" :: "l"(&g_progress) : "memory");
        __syncwarp();
        seq++;
        if (++st == NST) { st = 0; ph ^= 1; }
    }
    if (tid == 0) FK_STAMP(2);

    {
        float* o = red_s + warp * 128;
        o[16 * t + g]          = acc0[0] + acc1[0];
        o[16 * t + 8 + g]      = acc0[1] + acc1[1];
        o[64 + 16 * t + g]     = acc0[2] + acc1[2];
        o[64 + 16 * t + 8 + g] = acc0[3] + acc1[3];
        if (lane == 0) { ml_s[warp] = m_run; ml_s[8 + warp] = lacc[0]; }
    }
    __syncthreads();
    if (tid < DH) {
        const float4 ma = *reinterpret_cast<const float4*>(ml_s), mb = *reinterpret_cast<const float4*>(ml_s + 4);
        const float4 la = *reinterpret_cast<const float4*>(ml_s + 8), lb = *reinterpret_cast<const float4*>(ml_s + 12);
        const float mm[8] = {ma.x, ma.y, ma.z, ma.w, mb.x, mb.y, mb.z, mb.w};
        const float ll[8] = {la.x, la.y, la.z, la.w, lb.x, lb.y, lb.z, lb.w};
        float M = mm[0];
#pragma unroll
        for (int w = 1; w < 8; w++) M = fmaxf(M, mm[w]);
        float L = 0.f, o = 0.f;
#pragma unroll
        for (int w = 0; w < 8; w++) {
            const float f = ex2((mm[w] - M) * SC);
            L = fmaf(f, ll[w], L);
            o = fmaf(f, red_s[w * 128 + tid], o);
        }
        o_s[tid] = __float2bfloat16_rn(__fdividef(o, L));
    }
    __syncthreads();
    {
        float d[4][4];
#pragma unroll
        for (int kg = 0; kg < 4; kg++) { d[kg][0] = d[kg][1] = d[kg][2] = d[kg][3] = 0.f; }
        uint32_t pp[4][2];
        const __nv_bfloat16* op = o_s + (warp >> 2) * 64 + 2 * t;
#pragma unroll
        for (int kg = 0; kg < 4; kg++) {
            pp[kg][0] = *reinterpret_cast<const uint32_t*>(op + kg * 16);
            pp[kg][1] = *reinterpret_cast<const uint32_t*>(op + kg * 16 + 8);
        }
#pragma unroll
        for (int j = 0; j < 8; j++) {
            const uint32_t msk = (j == rsel ? 0x0000ffffu : 0u) | (j == (rsel ^ 1) ? 0xffff0000u : 0u);
#pragma unroll
            for (int kg = 0; kg < 4; kg++) mma_bf16(d[kg], wa[kg][j], pp[kg][0] & msk, pp[kg][1] & msk);
        }
        float r[4];
#pragma unroll
        for (int i = 0; i < 4; i++) r[i] = (d[0][i] + d[1][i]) + (d[2][i] + d[3][i]);
        {
        st_relaxed(a_out, make_uint4(__float_as_uint(r[0]), tag, __float_as_uint(r[1]), tag));
        st_relaxed(a_out + 4 * (2 * NH) * 8, make_uint4(__float_as_uint(r[2]), tag, __float_as_uint(r[3]), tag));
        }
    }
    if (tid == 0) FK_STAMP(3);
    if (warp == 0) {
        const uint4* p = &g_attn_part[((b * 32 + h) * (2 * NH) + q4 * 16) * 8 + cp];
        uint4 v[16];
#pragma unroll
        for (int i = 0; i < 16; i++) v[i] = ld_relaxed(p + i * 8);
        for (int spin = 0; spin < (1 << 20); spin++) {
            bool ok = true;
#pragma unroll
            for (int i = 0; i < 16; i++) {
                if (!ll_valid(v[i], tag)) { v[i] = ld_relaxed(p + i * 8); ok = false; }
            }
            if (ok) break;
            if (FK_POLLSLEEP) __nanosleep(FK_POLLSLEEP);
        }
        __syncwarp();
        float s0 = 0.f, s1 = 0.f;
#pragma unroll
        for (int i = 0; i < 16; i++) { s0 += __uint_as_float(v[i].x); s1 += __uint_as_float(v[i].z); }
        s0 += __shfl_xor_sync(0xffffffffu, s0, 8);  s1 += __shfl_xor_sync(0xffffffffu, s1, 8);
        s0 += __shfl_xor_sync(0xffffffffu, s0, 16); s1 += __shfl_xor_sync(0xffffffffu, s1, 16);
        if (lane < 8) {
            out[b * DM + h * 16 + cp]     = __float2bfloat16_rn(x0 + bf16r(bf16r(s0) * g0));
            out[b * DM + h * 16 + 8 + cp] = __float2bfloat16_rn(x1 + bf16r(bf16r(s1) * g1));
        }
        if (lane == 0) { g_epoch[cta] = tag + 1; FK_STAMP(4); }
    }
}

}

extern "C" void kernel_launch(void* const* d_in, const int* in_sizes, int n_in, void* d_out, int out_size) {
    (void)in_sizes; (void)n_in; (void)out_size;
    const __nv_bfloat16* x  = (const __nv_bfloat16*)d_in[0];
    const __nv_bfloat16* Kc = (const __nv_bfloat16*)d_in[1];
    const __nv_bfloat16* Vc = (const __nv_bfloat16*)d_in[2];
    const __nv_bfloat16* wq = (const __nv_bfloat16*)d_in[3];
    const __nv_bfloat16* wo = (const __nv_bfloat16*)d_in[4];
    const __nv_bfloat16* w1 = (const __nv_bfloat16*)d_in[6];
    const __nv_bfloat16* w2 = (const __nv_bfloat16*)d_in[7];
    static bool attr_set = false;
    if (!attr_set) {
        cudaFuncSetAttribute(fk::fused_decode_kernel, cudaFuncAttributeMaxDynamicSharedMemorySize, fk::SMEM_BYTES);
        attr_set = true;
    }
    fk::fused_decode_kernel<<<fk::N_CTA, fk::NTHREADS, fk::SMEM_BYTES>>>(x, Kc, Vc, wq, wo, w1, w2, (__nv_bfloat16*)d_out);
}
```

```cpp
#include <cuda_runtime.h>
#include <cuda.h>
#include <cuda_bf16.h>
#include <stdint.h>

namespace fk {

#define FK_NST 4
#define FK_FIRST 2
#define FK_PRE 1
#define FK_WTILE 1
#define FK_WSTEP 3
#define FK_LEAD 0
#define FK_ENDT 8
#define FK_LEAD_END 32

constexpr int NB = 4, NH = 32, SK = 8192, DH = 128, DM = 512, FF = 1376;
constexpr int TK = 128;
constexpr int NT = SK / TK;
constexpr int STAGE_BYTES = TK * DH * 2;
constexpr int NST = FK_NST;
constexpr int NCW = 8;
constexpr int NTHREADS = NCW * 32;
constexpr int N_ATT = NB * NH;
constexpr int N_FFN = 4;
constexpr int FS = FF / N_FFN;
constexpr int N_CTA = N_ATT + N_FFN;
constexpr int NSEQ = 2 * NT;
static_assert(NST % 2 == 0, "K tiles live in the even stages, V tiles in the odd ones");

constexpr int OFF_W   = NST * STAGE_BYTES;
constexpr int OFF_XN  = OFF_W;
constexpr int OFF_X   = OFF_W + 8192;
constexpr int OFF_RED = OFF_W + 12288;
constexpr int OFF_BAR = OFF_W + STAGE_BYTES;
constexpr int OFF_Q   = OFF_BAR + 256;
constexpr int OFF_ML  = OFF_Q + 256;
constexpr int OFF_O   = OFF_ML + 64;
constexpr int SMEM_ATT = OFF_O + 256;
constexpr int FFN_CHUNK = 64 * FS * 2;
constexpr int NBF = (NST >= 6) ? 4 : 2;
constexpr int FFN_XN = NBF * FFN_CHUNK, FFN_H = FFN_XN + 8192, FFN_RED = FFN_H + 5504, FFN_BAR = FFN_RED + 32768;
constexpr int SMEM_FFN = FFN_BAR + 64;
static_assert(FFN_CHUNK == 43 * DM * 2, "chunk geometry");
constexpr int SMEM_BYTES = SMEM_ATT > SMEM_FFN ? SMEM_ATT : SMEM_FFN;

__device__ __align__(256) uint4 g_q_part[NH * NB * 32];
__device__ __align__(256) uint4 g_attn_part[NB * 32 * NH * 8];
__device__ __align__(256) uint4 g_ffn_part[NB * 32 * N_FFN * 8];
__device__ __align__(256) uint32_t g_progress[64];
#define FK_ONE4 1u, 1u, 1u, 1u
#define FK_ONE16 FK_ONE4, FK_ONE4, FK_ONE4, FK_ONE4
#define FK_ONE64 FK_ONE16, FK_ONE16, FK_ONE16, FK_ONE16
__device__ __align__(256) uint32_t g_epoch[N_CTA] = {FK_ONE64, FK_ONE64, FK_ONE4};

__device__ __forceinline__ uint32_t smem_u32(const void* p) { return (uint32_t)__cvta_generic_to_shared(p); }

__device__ __forceinline__ void mbar_init(uint32_t bar, uint32_t cnt) {
    asm volatile("mbarrier.init.shared::cta.b64 [%0], %1;" :: "r"(bar), "r"(cnt) : "memory");
}
__device__ __forceinline__ void mbar_expect_tx(uint32_t bar, uint32_t bytes) {
    asm volatile("mbarrier.arrive.expect_tx.shared::cta.b64 _, [%0], %1;" :: "r"(bar), "r"(bytes) : "memory");
}
__device__ __forceinline__ uint32_t atom_inc_shared(uint32_t addr) {
    uint32_t old;
    asm volatile("atom.relaxed.cta.shared::cta.add.u32 %0, [%1], 1;" : "=r"(old) : "r"(addr) : "memory");
    return old;
}
__device__ __forceinline__ void mbar_wait(uint32_t bar, uint32_t parity) {
    asm volatile(
        "{\n"
        ".reg .pred p;\n"
        "FK_WAIT:\n"
        "mbarrier.try_wait.parity.shared::cta.b64 p, [%0], %1;\n"
        "@p bra FK_DONE;\n"
        "bra FK_WAIT;\n"
        "FK_DONE:\n"
        "}\n" :: "r"(bar), "r"(parity) : "memory");
}
__device__ __forceinline__ void bulk_load(uint32_t dst, const void* src, uint32_t bytes, uint32_t bar, uint64_t pol) {
    asm volatile("cp.async.bulk.shared::cluster.global.mbarrier::complete_tx::bytes.L2::cache_hint [%0], [%1], %2, [%3], %4;"
                 :: "r"(dst), "l"(src), "r"(bytes), "r"(bar), "l"(pol) : "memory");
}
__device__ __forceinline__ uint4 ldg_nc(const void* p) {
    uint4 v;
    asm volatile("ld.global.nc.L1::no_allocate.v4.u32 {%0,%1,%2,%3}, [%4];"
                 : "=r"(v.x), "=r"(v.y), "=r"(v.z), "=r"(v.w) : "l"(p));
    return v;
}
__device__ __forceinline__ void bulk_load_plain(uint32_t dst, const void* src, uint32_t bytes, uint32_t bar) {
    asm volatile("cp.async.bulk.shared::cluster.global.mbarrier::complete_tx::bytes [%0], [%1], %2, [%3];"
                 :: "r"(dst), "l"(src), "r"(bytes), "r"(bar) : "memory");
}
__device__ __forceinline__ void tma_load_2d(uint32_t dst, const CUtensorMap* map, int c0, int c1, uint32_t bar) {
    asm volatile("cp.async.bulk.tensor.2d.shared::cluster.global.mbarrier::complete_tx::bytes [%0], [%1, {%3, %4}], [%2];"
                 :: "r"(dst), "l"(map), "r"(bar), "r"(c0), "r"(c1) : "memory");
}
__device__ __forceinline__ uint32_t ldg_nc32(const void* p) {
    uint32_t v;
    asm volatile("ld.global.nc.L1::no_allocate.u32 %0, [%1];" : "=r"(v) : "l"(p));
    return v;
}
__device__ __forceinline__ uint32_t lds32(uint32_t addr) {
    uint32_t v;
    asm volatile("ld.volatile.shared.u32 %0, [%1];" : "=r"(v) : "r"(addr) : "memory");
    return v;
}
__device__ __forceinline__ uint32_t pin(uint32_t v) {
    uint32_t r;
    asm volatile("mov.b32 %0, %1;" : "=r"(r) : "r"(v));
    return r;
}
__device__ __forceinline__ uint32_t ld_relaxed32(const uint32_t* p) {
    uint32_t v;
    asm volatile("ld.relaxed.gpu.global.u32 %0, [%1];" : "=r"(v) : "l"(p) : "memory");
    return v;
}
__device__ __forceinline__ bool mbar_test(uint32_t bar, uint32_t parity) {
    uint32_t ok;
    asm volatile("{\n.reg .pred p;\nmbarrier.test_wait.parity.shared::cta.b64 p, [%1], %2;\nselp.u32 %0, 1, 0, p;\n}\n"
                 : "=r"(ok) : "r"(bar), "r"(parity) : "memory");
    return ok != 0;
}
__device__ __forceinline__ uint4 ld_relaxed(const uint4* p) {
    uint4 v;
    asm volatile("ld.relaxed.gpu.global.v4.u32 {%0,%1,%2,%3}, [%4];"
                 : "=r"(v.x), "=r"(v.y), "=r"(v.z), "=r"(v.w) : "l"(p) : "memory");
    return v;
}
__device__ __forceinline__ void st_relaxed(uint4* p, uint4 v) {
    asm volatile("st.relaxed.gpu.global.v4.u32 [%0], {%1,%2,%3,%4};"
                 :: "l"(p), "r"(v.x), "r"(v.y), "r"(v.z), "r"(v.w) : "memory");
}
__device__ __forceinline__ void ldsm_x4(uint32_t (&r)[4], uint32_t addr) {
    asm volatile("ldmatrix.sync.aligned.m8n8.x4.shared.b16 {%0,%1,%2,%3}, [%4];"
                 : "=r"(r[0]), "=r"(r[1]), "=r"(r[2]), "=r"(r[3]) : "r"(addr) : "memory");
}
__device__ __forceinline__ void ldsm_x4_t(uint32_t (&r)[4], uint32_t addr) {
    asm volatile("ldmatrix.sync.aligned.m8n8.x4.trans.shared.b16 {%0,%1,%2,%3}, [%4];"
                 : "=r"(r[0]), "=r"(r[1]), "=r"(r[2]), "=r"(r[3]) : "r"(addr) : "memory");
}
__device__ __forceinline__ void mma_bf16(float (&c)[4], const uint32_t (&a)[4], uint32_t b0, uint32_t b1) {
    asm volatile("mma.sync.aligned.m16n8k16.row.col.f32.bf16.bf16.f32 {%0,%1,%2,%3}, {%4,%5,%6,%7}, {%8,%9}, {%0,%1,%2,%3};"
                 : "+f"(c[0]), "+f"(c[1]), "+f"(c[2]), "+f"(c[3])
                 : "r"(a[0]), "r"(a[1]), "r"(a[2]), "r"(a[3]), "r"(b0), "r"(b1));
}
__device__ __forceinline__ float ex2(float x) {
    float r;
    asm("ex2.approx.ftz.f32 %0, %1;" : "=f"(r) : "f"(x));
    return r;
}
__device__ __forceinline__ uint32_t pack_bf16(float lo, float hi) {
    uint32_t r;
    asm("cvt.rn.bf16x2.f32 %0, %1, %2;" : "=r"(r) : "f"(hi), "f"(lo));
    return r;
}
__device__ __forceinline__ float bf_lo(uint32_t w) { return __uint_as_float(w << 16); }
__device__ __forceinline__ float bf_hi(uint32_t w) { return __uint_as_float(w & 0xffff0000u); }
__device__ __forceinline__ float bf16r(float x) { return __bfloat162float(__float2bfloat16_rn(x)); }
__device__ __forceinline__ float silu_f(float x) { return x / (1.0f + __expf(-x)); }

__device__ __forceinline__ void warp_layernorm(const uint4 a, const uint4 b, float (&xn)[16]) {
    float v[16];
    v[0] = bf_lo(a.x); v[1] = bf_hi(a.x); v[2] = bf_lo(a.y); v[3] = bf_hi(a.y);
    v[4] = bf_lo(a.z); v[5] = bf_hi(a.z); v[6] = bf_lo(a.w); v[7] = bf_hi(a.w);
    v[8] = bf_lo(b.x); v[9] = bf_hi(b.x); v[10] = bf_lo(b.y); v[11] = bf_hi(b.y);
    v[12] = bf_lo(b.z); v[13] = bf_hi(b.z); v[14] = bf_lo(b.w); v[15] = bf_hi(b.w);
    float s = 0.f;
#pragma unroll
    for (int i = 0; i < 16; i++) s += v[i];
#pragma unroll
    for (int o = 16; o; o >>= 1) s += __shfl_xor_sync(0xffffffffu, s, o);
    const float mean = s * (1.0f / DM);
    float ss = 0.f;
#pragma unroll
    for (int i = 0; i < 16; i++) { const float d = v[i] - mean; ss = fmaf(d, d, ss); }
#pragma unroll
    for (int o = 16; o; o >>= 1) ss += __shfl_xor_sync(0xffffffffu, ss, o);
    const float m_bf = bf16r(mean);
    const float den = bf16r(sqrtf(bf16r(bf16r(ss * (1.0f / DM)) + 1e-5f)));
#pragma unroll
    for (int i = 0; i < 16; i++) xn[i] = bf16r(__fdiv_rn(bf16r(v[i] - m_bf), den));
}

__device__ __forceinline__ bool ll_valid(const uint4& v, uint32_t tag) { return v.y == tag && v.w == tag; }

__device__ __forceinline__ void ffn_cta(uint8_t* smem, int f, uint32_t tag,
                                        const __nv_bfloat16* __restrict__ x,
                                        const __nv_bfloat16* __restrict__ w1,
                                        const __nv_bfloat16* __restrict__ w2) {
    const int tid = threadIdx.x, warp = tid >> 5, lane = tid & 31;
    const uint32_t sbase = smem_u32(smem), bar = sbase + FFN_BAR;
    float* xnT = reinterpret_cast<float*>(smem + FFN_XN);
    float* hT  = reinterpret_cast<float*>(smem + FFN_H);
    float* red = reinterpret_cast<float*>(smem + FFN_RED);
    if (tid == 0) {
#pragma unroll
        for (int s = 0; s < NBF; s++) mbar_init(bar + s * 8, 1);
    }
    __syncthreads();
    auto issue = [&](int c) {
        const int s = c % NBF;
        if (tid == 0) mbar_expect_tx(bar + s * 8, FFN_CHUNK);
        if (c < 8) {
            __syncthreads();
            if (tid < 64) bulk_load_plain(sbase + s * FFN_CHUNK + tid * (FS * 2), w1 + (size_t)(c * 64 + tid) * FF + f * FS, FS * 2, bar + s * 8);
        } else if (tid == 0) {
            bulk_load_plain(sbase + s * FFN_CHUNK, w2 + (size_t)(f * FS + (c - 8) * 43) * DM, FFN_CHUNK, bar + s * 8);
        }
    };
    for (int c = 0; c < NBF; c++) issue(c);
    if (warp < NB) {
        float xn[16];
        const uint4 xa = ldg_nc(x + warp * DM + lane * 16), xb = ldg_nc(x + warp * DM + lane * 16 + 8);
        warp_layernorm(xa, xb, xn);
#pragma unroll
        for (int i = 0; i < 16; i++) xnT[(lane * 16 + i) * 4 + warp] = xn[i];
    }
    __syncthreads();
    float acc[4][8];
#pragma unroll
    for (int b = 0; b < 4; b++)
#pragma unroll
        for (int c = 0; c < 8; c++) acc[b][c] = 0.f;
#pragma unroll 1
    for (int c = 0; c < 16; c++) {
        const int s = c % NBF;
        mbar_wait(bar + s * 8, (c / NBF) & 1);
        const bool st1 = c < 8;
        const int cg = st1 ? tid % 43 : (tid & 63), r0 = st1 ? tid / 43 : (tid >> 6);
        const int rstep = st1 ? 5 : 4, nrows = st1 ? 64 : 43, rbytes = st1 ? FS * 2 : DM * 2;
        const float* vec = st1 ? xnT + c * 64 * 4 : hT + (c - 8) * 43 * 4;
        const uint8_t* wb = smem + s * FFN_CHUNK + cg * 16;
        if (!st1 || tid < 43 * 5) {
#pragma unroll 2
            for (int k = r0; k < nrows; k += rstep) {
                const uint4 w = *reinterpret_cast<const uint4*>(wb + k * rbytes);
                const float4 xv = *reinterpret_cast<const float4*>(vec + k * 4);
                const float wf[8] = {bf_lo(w.x), bf_hi(w.x), bf_lo(w.y), bf_hi(w.y), bf_lo(w.z), bf_hi(w.z), bf_lo(w.w), bf_hi(w.w)};
#pragma unroll
                for (int j = 0; j < 8; j++) {
                    acc[0][j] = fmaf(xv.x, wf[j], acc[0][j]);
                    acc[1][j] = fmaf(xv.y, wf[j], acc[1][j]);
                    acc[2][j] = fmaf(xv.z, wf[j], acc[2][j]);
                    acc[3][j] = fmaf(xv.w, wf[j], acc[3][j]);
                }
            }
        }
        __syncthreads();
        if (c + NBF < 16) issue(c + NBF);
        if (c == 7) {
            if (tid < 43 * 5) {
#pragma unroll
                for (int b = 0; b < 4; b++)
#pragma unroll
                    for (int j = 0; j < 8; j++) red[(r0 * 4 + b) * FS + cg * 8 + j] = acc[b][j];
            }
#pragma unroll
            for (int b = 0; b < 4; b++)
#pragma unroll
                for (int j = 0; j < 8; j++) acc[b][j] = 0.f;
            __syncthreads();
            for (int i = tid; i < 4 * FS; i += NTHREADS) {
                const int b = i / FS, cc = i % FS;
                float sum = 0.f;
#pragma unroll
                for (int ks = 0; ks < 5; ks++) sum += red[(ks * 4 + b) * FS + cc];
                hT[cc * 4 + b] = bf16r(silu_f(bf16r(sum)));
            }
            __syncthreads();
        }
    }
    {
        const int cg = tid & 63, fs = tid >> 6;
#pragma unroll
        for (int b = 0; b < 4; b++)
#pragma unroll
            for (int j = 0; j < 8; j++) red[(fs * 4 + b) * DM + cg * 8 + j] = acc[b][j];
    }
    __syncthreads();
    for (int i = tid; i < NB * 256; i += NTHREADS) {
        const int b = i >> 8, j = (i >> 3) & 31, p = i & 7;
        float s0 = 0.f, s1 = 0.f;
#pragma unroll
        for (int fs = 0; fs < 4; fs++) { s0 += red[(fs * 4 + b) * DM + 16 * j + p]; s1 += red[(fs * 4 + b) * DM + 16 * j + 8 + p]; }
        st_relaxed(&g_ffn_part[((b * 32 + j) * N_FFN + f) * 8 + p],
                   make_uint4(__float_as_uint(s0), tag, __float_as_uint(s1), tag));
    }
}

__global__ void __launch_bounds__(NTHREADS, 1)
fused_decode_kernel(const __grid_constant__ CUtensorMap wo_map,
                    const __nv_bfloat16* __restrict__ x, const __nv_bfloat16* __restrict__ Kc,
                    const __nv_bfloat16* __restrict__ Vc, const __nv_bfloat16* __restrict__ wq,
                    const __nv_bfloat16* __restrict__ wo, const __nv_bfloat16* __restrict__ w1,
                    const __nv_bfloat16* __restrict__ w2, __nv_bfloat16* __restrict__ out) {
    extern __shared__ __align__(1024) uint8_t smem[];
    const int cta = blockIdx.x;
    const int tid = threadIdx.x, warp = tid >> 5, lane = tid & 31;
    if (cta >= N_ATT) {
        const uint32_t tag = ld_relaxed32(&g_epoch[cta]);
        ffn_cta(smem, cta - N_ATT, tag, x, w1, w2);
        if (tid == 0) { g_epoch[cta] = tag + 1; }
        return;
    }

    const int b = cta & 3, h = cta >> 2;
    const int bh = b * NH + h;
    const uint32_t sbase = pin(smem_u32(smem));
    const uint32_t bar_full = sbase + OFF_BAR;
    const uint32_t cnt_rel = bar_full + NST * 8;
    const char* kp = reinterpret_cast<const char*>(Kc) + (size_t)bh * SK * DH * 2;
    const char* vp = reinterpret_cast<const char*>(Vc) + (size_t)bh * SK * DH * 2;
    const char* wop = reinterpret_cast<const char*>(wo) + (size_t)h * DH * DM * 2;
    uint64_t pol;
    asm volatile("createpolicy.fractional.L2::evict_first.b64 %0, 1.0;" : "=l"(pol));
    auto issue_kv = [&](const char* src, int s) {
        const uint32_t bar = bar_full + s * 8;
        mbar_expect_tx(bar, STAGE_BYTES);
        bulk_load(sbase + s * STAGE_BYTES, src, STAGE_BYTES, bar, pol);
    };
    auto issue_first = [&](int n) { issue_kv(((n & 1) ? vp : kp) + (size_t)(n >> 1) * STAGE_BYTES, n); };
    const uint32_t bar_w = bar_full + 216, cnt_w = bar_full + 224;
    auto issue_w = [&](int q) {
        mbar_expect_tx(bar_w, STAGE_BYTES);
#pragma unroll 1
        for (int c = 0; c < 8; c++) tma_load_2d(sbase + OFF_W + c * 4096, &wo_map, c * 64, h * DH + q * 32, bar_w);
    };

    const int g = lane >> 2, t = lane & 3;
    float* xn_s  = reinterpret_cast<float*>(smem + OFF_XN);
    float* red_s = reinterpret_cast<float*>(smem + OFF_RED);
    __nv_bfloat16* q_s = reinterpret_cast<__nv_bfloat16*>(smem + OFF_Q);
    float* ml_s = reinterpret_cast<float*>(smem + OFF_ML);
    __nv_bfloat16* o_s = reinterpret_cast<__nv_bfloat16*>(smem + OFF_O);

    uint4* const q_out = &g_q_part[(h * NB + (lane >> 3)) * 32 + b * 8 + (lane & 7)];
    uint4* const a_out = &g_attn_part[((b * 32 + warp * 4 + t) * NH + h) * 8 + g];

    volatile uint32_t* q_flag = reinterpret_cast<volatile uint32_t*>(smem + OFF_BAR + 192);
    const uint32_t bar_x = bar_full + 200;
    if (tid == 0) {
        mbar_init(bar_full, 1);
        issue_first(0);
        mbar_init(bar_x, 1);
        mbar_expect_tx(bar_x, NB * DM * 2);
        bulk_load_plain(sbase + OFF_X, x, NB * DM * 2, bar_x);
#pragma unroll
        for (int s = 1; s < NST; s++) mbar_init(bar_full + s * 8, 1);
        mbar_init(bar_w, 1);
#pragma unroll
        for (int s = 0; s < NST; s++) *reinterpret_cast<volatile uint32_t*>(smem + OFF_BAR + NST * 8 + s * 4) = 0;
        *reinterpret_cast<volatile uint32_t*>(smem + OFF_BAR + 224) = 0;
        *q_flag = 0;
#pragma unroll 1
        for (int s = 1; s < FK_PRE; s++) issue_first(s);
    }
    uint32_t qf[8][2];
    uint32_t tag;
    {
        uint32_t w[32];
        const __nv_bfloat16* wp = wq + (size_t)(warp * 64 + (lane >> 4) * 32) * (NH * DH) + h * DH + b * 32 + (lane & 15) * 2;
#pragma unroll
        for (int i = 0; i < 32; i++) w[i] = ldg_nc32(wp + (size_t)i * (NH * DH));
        tag = ld_relaxed32(&g_epoch[cta]);
        if (tid == 0) {
#pragma unroll 1
            for (int s = FK_PRE; s < FK_FIRST; s++) issue_first(s);
            asm volatile("prefetch.tensormap [%0];" :: "l"(&wo_map) : "memory");
            asm volatile("prefetch.global.L2 [%0];" :: "l"(wop));
        }
        if (warp == 0) st_relaxed(q_out, make_uint4(0, 0, 0, 0));
        st_relaxed(a_out, make_uint4(0, 0, 0, 0));
        __syncthreads();
        if (warp < 4) {
            float xn[16];
            mbar_wait(bar_x, 0);
            const uint4 xa = *reinterpret_cast<const uint4*>(smem + OFF_X + warp * DM * 2 + lane * 32);
            const uint4 xb = *reinterpret_cast<const uint4*>(smem + OFF_X + warp * DM * 2 + lane * 32 + 16);
            warp_layernorm(xa, xb, xn);
#pragma unroll
            for (int i = 0; i < 16; i += 4)
                *reinterpret_cast<float4*>(xn_s + warp * DM + lane * 16 + i) = make_float4(xn[i], xn[i + 1], xn[i + 2], xn[i + 3]);
        }
        __syncthreads();
        float acc[4][2];
#pragma unroll
        for (int bb = 0; bb < 4; bb++) acc[bb][0] = acc[bb][1] = 0.f;
        const float* xp = xn_s + warp * 64 + (lane >> 4) * 32;
#pragma unroll
        for (int i4 = 0; i4 < 8; i4++) {
#pragma unroll
            for (int bb = 0; bb < 4; bb++) {
                const float4 xv = *reinterpret_cast<const float4*>(xp + bb * DM + i4 * 4);
                const float xs[4] = {xv.x, xv.y, xv.z, xv.w};
#pragma unroll
                for (int u = 0; u < 4; u++) {
                    acc[bb][0] = fmaf(xs[u], bf_lo(w[i4 * 4 + u]), acc[bb][0]);
                    acc[bb][1] = fmaf(xs[u], bf_hi(w[i4 * 4 + u]), acc[bb][1]);
                }
            }
        }
        const bool up = lane >= 16;
        float k0 = up ? acc[2][0] : acc[0][0], k1 = up ? acc[2][1] : acc[0][1];
        float k2 = up ? acc[3][0] : acc[1][0], k3 = up ? acc[3][1] : acc[1][1];
        k0 += __shfl_xor_sync(0xffffffffu, up ? acc[0][0] : acc[2][0], 16);
        k1 += __shfl_xor_sync(0xffffffffu, up ? acc[0][1] : acc[2][1], 16);
        k2 += __shfl_xor_sync(0xffffffffu, up ? acc[1][0] : acc[3][0], 16);
        k3 += __shfl_xor_sync(0xffffffffu, up ? acc[1][1] : acc[3][1], 16);
        float* rp = red_s + warp * 128 + (up ? 64 : 0) + (lane & 15) * 2;
        *reinterpret_cast<float2*>(rp)      = make_float2(k0, k1);
        *reinterpret_cast<float2*>(rp + 32) = make_float2(k2, k3);
        __syncthreads();
        if (warp == 0) {
            float4 s = make_float4(0.f, 0.f, 0.f, 0.f);
#pragma unroll
            for (int w8 = 0; w8 < NCW; w8++) {
                const float4 v = *reinterpret_cast<const float4*>(red_s + w8 * 128 + lane * 4);
                s.x += v.x; s.y += v.y; s.z += v.z; s.w += v.w;
            }
            st_relaxed(q_out, make_uint4(pack_bf16(s.x, s.y), tag, pack_bf16(s.z, s.w), tag));
            const uint4* p = &g_q_part[(h * NB + b) * 32 + lane];
            uint4 v = ld_relaxed(p);
            for (int spin = 0; !ll_valid(v, tag) && spin < (1 << 20); spin++) v = ld_relaxed(p);
            *reinterpret_cast<uint2*>(q_s + lane * 4) = make_uint2(v.x, v.z);
            if (lane == 0) *q_flag = 1;
        }
        if (tid == NTHREADS - 32) {
            int next = FK_FIRST, watch = 0;
            while (next < NST) {
                if (mbar_test(bar_full + watch * 8, 0)) { issue_first(next); next++; watch++; }
                else if (*q_flag) break;
            }
#pragma unroll 1
            for (; next < NST; next++) issue_first(next);
        }
        __syncthreads();
#pragma unroll
        for (int j = 0; j < 8; j++) {
            const int c = (j ^ g) & 7;
            qf[j][0] = *reinterpret_cast<const uint32_t*>(q_s + c * 8 + 2 * t);
            qf[j][1] = *reinterpret_cast<const uint32_t*>(q_s + 64 + c * 8 + 2 * t);
        }
    }

    constexpr float RSQRT_DH = 0.08838834764831845f, LOG2E = 1.4426950408889634f;
    const int li = lane & 7, lm = lane >> 3;
    const uint32_t k_base = pin(sbase + (uint32_t)((warp * 16 + li + 8 * (lm & 1)) * 256 + (lm >> 1) * 128 + li * 16));
    const uint32_t v_base = pin(sbase + (uint32_t)((warp * 16 + li + 8 * (lm >> 1)) * 256 + (lm & 1) * 128 + li * 16));
    const bool diag = (t == (g >> 1));
    uint32_t msk[8];
#pragma unroll
    for (int j = 0; j < 8; j++) msk[j] = pin((j == (g ^ (2 * t)) ? 0x0000ffffu : 0u) | (j == (g ^ (2 * t) ^ 1) ? 0xffff0000u : 0u));
    const uint32_t ones[4] = {0x3f803f80u, 0x3f803f80u, 0x3f803f80u, 0x3f803f80u};

    float acc0[4] = {0.f, 0.f, 0.f, 0.f}, acc1[4] = {0.f, 0.f, 0.f, 0.f}, lacc[4] = {0.f, 0.f, 0.f, 0.f};
    float m_run = -INFINITY, fin_scale = 0.f;
    int st = 0; uint32_t ph = 0;
    int seq = NST;
    uint32_t wa[8][4][4];
    float g0 = 0.f, g1 = 0.f;
    uint4 gv = make_uint4(0, 0, 0, 0);
    const int cp = lane & 7, q4 = lane >> 3;
    const float x0 = __bfloat162float(reinterpret_cast<const __nv_bfloat16*>(smem + OFF_X)[b * DM + h * 16 + cp]);
    const float x1 = __bfloat162float(reinterpret_cast<const __nv_bfloat16*>(smem + OFF_X)[b * DM + h * 16 + 8 + cp]);
    const uint32_t prog_base = (tag - 1) * (uint32_t)(N_ATT * NT);
    const uint32_t prog_s = bar_full + 208;
    uint32_t prog_v = prog_base;
    if (tid == 0) *reinterpret_cast<volatile uint32_t*>(smem + OFF_BAR + 208) = prog_base;
    __syncthreads();
    auto pace = [&](uint32_t pv, uint32_t lim) {
        for (int spin = 0; (int)(pv - lim) < 0 && spin < 4096; spin++) pv = ld_relaxed32(&g_progress[0]);
    };

#pragma unroll 1
    for (int it = 0; it < NT; it++) {
#pragma unroll
        for (int q = 0; q <= 4; q++) {
            if (it == FK_WTILE + q * FK_WSTEP) {
                if (q == 0) {
                    if (tid == 0) {
                        asm volatile("fence.proxy.async.shared::cta;" ::: "memory");
                        issue_w(0);
                    }
                } else {
                    mbar_wait(bar_w, (q - 1) & 1);
                    const uint32_t wb = sbase + OFF_W + warp * 4096 + (li + 8 * (lane >> 4)) * 128;
#pragma unroll
                    for (int j = 0; j < 4; j++) {
                        const uint32_t ch = (uint32_t)(((2 * j + (lm & 1)) ^ li) << 4);
                        ldsm_x4_t(wa[2 * q - 2][j], wb + ch);
                        ldsm_x4_t(wa[2 * q - 1][j], wb + 2048 + ch);
                    }
                    if (q < 4 && lane == 0) {
                        const uint32_t rel = atom_inc_shared(cnt_w);
                        if ((rel & (NCW - 1)) == NCW - 1) issue_w(q);
                    }
                }
                __syncwarp();
            }
        }
        if (it == NT - 12 && warp == 0) {
            gv = ld_relaxed(&g_ffn_part[((b * 32 + h) * N_FFN + q4) * 8 + cp]);
        }
        if (it == NT - 2 && warp == 0) {
            const uint4* p = &g_ffn_part[((b * 32 + h) * N_FFN + q4) * 8 + cp];
            uint4 v = gv;
            for (int spin = 0; !ll_valid(v, tag) && spin < (1 << 20); spin++) { __nanosleep(64); v = ld_relaxed(p); }
            __syncwarp();
            g0 = __uint_as_float(v.x); g1 = __uint_as_float(v.z);
            g0 += __shfl_xor_sync(0xffffffffu, g0, 8);  g1 += __shfl_xor_sync(0xffffffffu, g1, 8);
            g0 += __shfl_xor_sync(0xffffffffu, g0, 16); g1 += __shfl_xor_sync(0xffffffffu, g1, 16);
            g0 = bf16r(silu_f(bf16r(g0))); g1 = bf16r(silu_f(bf16r(g1)));
        }
        if (tid == 0) {
            *reinterpret_cast<volatile uint32_t*>(smem + OFF_BAR + 208) = prog_v;
            prog_v = ld_relaxed32(&g_progress[0]);
        }
        const bool endgame = it >= NT - FK_ENDT;
        const char* k_next = kp + (size_t)(it + NST / 2) * STAGE_BYTES;
        const char* v_next = vp + (size_t)(it + NST / 2) * STAGE_BYTES;
        mbar_wait(bar_full + st * 8, ph);
        float c0[4] = {0.f, 0.f, 0.f, 0.f}, c1[4] = {0.f, 0.f, 0.f, 0.f};
        uint32_t relK = 0, pvK = 0;
        const uint32_t kb = k_base + st * STAGE_BYTES;
        {
#pragma unroll
            for (int j = 0; j < 8; j++) {
                uint32_t a[4];
                ldsm_x4(a, kb ^ (j << 4));
                mma_bf16((j & 1) ? c1 : c0, a, qf[j][0], qf[j][1]);
            }
            if (!endgame && seq < NSEQ && lane == 0) {
                relK = atom_inc_shared(cnt_rel + st * 4);
                pvK = lds32(prog_s);
            }
        }
        float s0 = (g & 1) ? (c0[1] + c1[1]) : (c0[0] + c1[0]);
        float s1 = (g & 1) ? (c0[3] + c1[3]) : (c0[2] + c1[2]);
        {
            const uint32_t r1 = pack_bf16(s0, s1);
            const uint32_t r2 = pack_bf16(bf_lo(r1) * RSQRT_DH, bf_hi(r1) * RSQRT_DH);
            s0 = diag ? bf_lo(r2) : -INFINITY;
            s1 = diag ? bf_hi(r2) : -INFINITY;
        }
        int key = __float_as_int(fmaxf(s0, s1));
        key ^= (key >> 31) & 0x7fffffff;
        key = __reduce_max_sync(0xffffffffu, key);
        key ^= (key >> 31) & 0x7fffffff;
        const float tmax = __int_as_float(key);
        if (tmax > m_run) {
            const float sc = ex2((m_run - tmax) * LOG2E);
#pragma unroll
            for (int i = 0; i < 4; i++) { acc0[i] *= sc; acc1[i] *= sc; }
            lacc[0] *= sc;
            m_run = tmax;
        }
        const float mc = -m_run * LOG2E;
        const uint32_t pk = pack_bf16(ex2(fmaf(s0, LOG2E, mc)), ex2(fmaf(s1, LOG2E, mc)));
        const uint32_t xx = __shfl_sync(0xffffffffu, pk, 9 * t), yy = __shfl_sync(0xffffffffu, pk, 9 * t + 4);
        const uint32_t pp0 = __byte_perm(xx, yy, 0x5410), pp1 = __byte_perm(xx, yy, 0x7632);
        if ((relK & (NCW - 1)) == NCW - 1) {
            pace(pvK, prog_base + (uint32_t)(it * N_ATT - (FK_LEAD)));
            issue_kv(k_next, st);
        }
        __syncwarp();
        const int stK = st;
        seq++;
        if (++st == NST) { st = 0; ph ^= 1; }
        mma_bf16(lacc, ones, pp0, pp1);
        if (it == NT - 1) {
            if (lane == 0) { ml_s[warp] = m_run; ml_s[8 + warp] = lacc[0]; }
            __syncthreads();
            const float4 ma = *reinterpret_cast<const float4*>(ml_s), mb = *reinterpret_cast<const float4*>(ml_s + 4);
            const float4 la = *reinterpret_cast<const float4*>(ml_s + 8), lb = *reinterpret_cast<const float4*>(ml_s + 12);
            const float M = fmaxf(fmaxf(fmaxf(ma.x, ma.y), fmaxf(ma.z, ma.w)), fmaxf(fmaxf(mb.x, mb.y), fmaxf(mb.z, mb.w)));
            const float L = (ex2((ma.x - M) * LOG2E) * la.x + ex2((ma.y - M) * LOG2E) * la.y) + (ex2((ma.z - M) * LOG2E) * la.z + ex2((ma.w - M) * LOG2E) * la.w)
                          + (ex2((mb.x - M) * LOG2E) * lb.x + ex2((mb.y - M) * LOG2E) * lb.y) + (ex2((mb.z - M) * LOG2E) * lb.z + ex2((mb.w - M) * LOG2E) * lb.w);
            fin_scale = __fdividef(ex2((m_run - M) * LOG2E), L);
        }
        mbar_wait(bar_full + st * 8, ph);
        const uint32_t vb = v_base + st * STAGE_BYTES;
        {
            uint32_t relV = 0, pvV = 0;
#pragma unroll
            for (int j = 0; j < 8; j++) {
                uint32_t a[4];
                ldsm_x4_t(a, vb ^ (j << 4));
                mma_bf16((j & 1) ? acc1 : acc0, a, pp0 & msk[j], pp1 & msk[j]);
            }
            if (seq - (endgame ? 1 : 0) < NSEQ && lane == 0) {
                relV = atom_inc_shared(cnt_rel + st * 4);
                pvV = lds32(prog_s);
            }
            if (tid == NTHREADS - 32) asm volatile("red.relaxed.gpu.global.add.u32 [%0], 1;" :: "l"(&g_progress[0]) : "memory");
            if ((relV & (NCW - 1)) == NCW - 1) {
                if (endgame) {
                    pace(pvV, prog_base + (uint32_t)((it + 1) * N_ATT - (FK_LEAD_END)));
                    issue_kv(k_next, stK);
                }
                if (seq < NSEQ) issue_kv(v_next, st);
            }
        }
        __syncwarp();
        seq++;
        if (++st == NST) { st = 0; ph ^= 1; }
    }

    {
        float* o = red_s + warp * 128;
        o[16 * t + g]          = (acc0[0] + acc1[0]) * fin_scale;
        o[16 * t + 8 + g]      = (acc0[1] + acc1[1]) * fin_scale;
        o[64 + 16 * t + g]     = (acc0[2] + acc1[2]) * fin_scale;
        o[64 + 16 * t + 8 + g] = (acc0[3] + acc1[3]) * fin_scale;
    }
    __syncthreads();
    if (tid < DH) {
        float v[8];
#pragma unroll
        for (int w = 0; w < 8; w++) v[w] = red_s[w * 128 + tid];
        const float o = ((v[0] + v[1]) + (v[2] + v[3])) + ((v[4] + v[5]) + (v[6] + v[7]));
        o_s[((tid >> 1) & 3) * 32 + (tid >> 4) * 4 + ((tid >> 3) & 1) * 2 + (tid & 1)] = __float2bfloat16_rn(o);
    }
    __syncthreads();
    {
        float d[4][4];
#pragma unroll
        for (int j = 0; j < 4; j++) { d[j][0] = d[j][1] = d[j][2] = d[j][3] = 0.f; }
        uint4 ov[4];
#pragma unroll
        for (int i = 0; i < 4; i++) ov[i] = *reinterpret_cast<const uint4*>(o_s + t * 32 + i * 8);
#pragma unroll
        for (int i = 0; i < 4; i++) {
#pragma unroll
            for (int j = 0; j < 4; j++) mma_bf16(d[j], wa[2 * i][j], ov[i].x, ov[i].y);
#pragma unroll
            for (int j = 0; j < 4; j++) mma_bf16(d[j], wa[2 * i + 1][j], ov[i].z, ov[i].w);
        }
        float r0 = d[0][0], r1 = d[0][2];
        if (t == 1) { r0 = d[1][0]; r1 = d[1][2]; }
        if (t == 2) { r0 = d[2][0]; r1 = d[2][2]; }
        if (t == 3) { r0 = d[3][0]; r1 = d[3][2]; }
        st_relaxed(a_out, make_uint4(__float_as_uint(r0), tag, __float_as_uint(r1), tag));
    }
    if (warp == 0) {
        const uint4* p = &g_attn_part[((b * 32 + h) * NH + q4 * 8) * 8 + cp];
        uint4 v[8];
#pragma unroll
        for (int i = 0; i < 8; i++) v[i] = ld_relaxed(p + i * 8);
        for (int spin = 0; spin < (1 << 20); spin++) {
            bool ok = true;
#pragma unroll
            for (int i = 0; i < 8; i++) {
                if (!ll_valid(v[i], tag)) { v[i] = ld_relaxed(p + i * 8); ok = false; }
            }
            if (ok) break;
        }
        __syncwarp();
        float s0 = ((__uint_as_float(v[0].x) + __uint_as_float(v[1].x)) + (__uint_as_float(v[2].x) + __uint_as_float(v[3].x)))
                 + ((__uint_as_float(v[4].x) + __uint_as_float(v[5].x)) + (__uint_as_float(v[6].x) + __uint_as_float(v[7].x)));
        float s1 = ((__uint_as_float(v[0].z) + __uint_as_float(v[1].z)) + (__uint_as_float(v[2].z) + __uint_as_float(v[3].z)))
                 + ((__uint_as_float(v[4].z) + __uint_as_float(v[5].z)) + (__uint_as_float(v[6].z) + __uint_as_float(v[7].z)));
        s0 += __shfl_xor_sync(0xffffffffu, s0, 8);  s1 += __shfl_xor_sync(0xffffffffu, s1, 8);
        s0 += __shfl_xor_sync(0xffffffffu, s0, 16); s1 += __shfl_xor_sync(0xffffffffu, s1, 16);
        if (lane < 8) {
            out[b * DM + h * 16 + cp]     = __float2bfloat16_rn(x0 + bf16r(bf16r(s0) * g0));
            out[b * DM + h * 16 + 8 + cp] = __float2bfloat16_rn(x1 + bf16r(bf16r(s1) * g1));
        }
        if (lane == 0) { g_epoch[cta] = tag + 1; }
    }
}

}

extern "C" void kernel_launch(void* const* d_in, const int* in_sizes, int n_in, void* d_out, int out_size) {
    (void)in_sizes; (void)n_in; (void)out_size;
    const __nv_bfloat16* x  = (const __nv_bfloat16*)d_in[0];
    const __nv_bfloat16* Kc = (const __nv_bfloat16*)d_in[1];
    const __nv_bfloat16* Vc = (const __nv_bfloat16*)d_in[2];
    const __nv_bfloat16* wq = (const __nv_bfloat16*)d_in[3];
    const __nv_bfloat16* wo = (const __nv_bfloat16*)d_in[4];
    const __nv_bfloat16* w1 = (const __nv_bfloat16*)d_in[6];
    const __nv_bfloat16* w2 = (const __nv_bfloat16*)d_in[7];

    typedef CUresult (*EncodeFn)(CUtensorMap*, CUtensorMapDataType, cuuint32_t, void*, const cuuint64_t*, const cuuint64_t*,
                                 const cuuint32_t*, const cuuint32_t*, CUtensorMapInterleave, CUtensorMapSwizzle,
                                 CUtensorMapL2promotion, CUtensorMapFloatOOBfill);
    static EncodeFn encode = nullptr;
    if (!encode) {
        cudaFuncSetAttribute(fk::fused_decode_kernel, cudaFuncAttributeMaxDynamicSharedMemorySize, fk::SMEM_BYTES);
        void* fn = nullptr;
        cudaDriverEntryPointQueryResult qr;
        cudaGetDriverEntryPoint("cuTensorMapEncodeTiled", &fn, cudaEnableDefault, &qr);
        encode = (EncodeFn)fn;
    }
    alignas(64) CUtensorMap wo_map;
    const cuuint64_t gdim[2] = {(cuuint64_t)fk::DM, (cuuint64_t)(fk::NH * fk::DH)};
    const cuuint64_t gstr[1] = {(cuuint64_t)(fk::DM * 2)};
    const cuuint32_t box[2] = {64u, 32u};
    const cuuint32_t estr[2] = {1u, 1u};
    encode(&wo_map, CU_TENSOR_MAP_DATA_TYPE_BFLOAT16, 2, (void*)wo, gdim, gstr, box, estr, CU_TENSOR_MAP_INTERLEAVE_NONE,
           CU_TENSOR_MAP_SWIZZLE_128B, CU_TENSOR_MAP_L2_PROMOTION_L2_128B, CU_TENSOR_MAP_FLOAT_OOB_FILL_NONE);

    fk::fused_decode_kernel<<<fk::N_CTA, fk::NTHREADS, fk::SMEM_BYTES>>>(wo_map, x, Kc, Vc, wq, wo, w1, w2, (__nv_bfloat16*)d_out);
}
```

```cpp
#include <cuda_runtime.h>
#include <cuda_bf16.h>
#include <stdint.h>

namespace fk {

#define FK_NST 4
#define FK_FIRST 2
#define FK_PRE 1
#define FK_WTILE 1
#define FK_WSTEP 3
#define FK_LEAD 0
#define FK_ENDT 8
#define FK_LEAD_END 32

constexpr int NB = 4, NH = 32, SK = 8192, DH = 128, DM = 512, FF = 1376;
constexpr int TK = 128;
constexpr int NT = SK / TK;
constexpr int STAGE_BYTES = TK * DH * 2;
constexpr int NST = FK_NST;
constexpr int NCW = 8;
constexpr int NTHREADS = NCW * 32;
constexpr int N_ATT = NB * NH;
constexpr int N_FFN = 4;
constexpr int FS = FF / N_FFN;
constexpr int N_CTA = N_ATT + N_FFN;
constexpr int NSEQ = 2 * NT;
static_assert(NST % 2 == 0, "K tiles live in the even stages, V tiles in the odd ones");

constexpr int OFF_W   = NST * STAGE_BYTES;
constexpr int OFF_XN  = OFF_W;
constexpr int OFF_X   = OFF_W + 8192;
constexpr int OFF_RED = OFF_W + 12288;
constexpr int OFF_BAR = OFF_W + STAGE_BYTES;
constexpr int OFF_Q   = OFF_BAR + 256;
constexpr int OFF_ML  = OFF_Q + 256;
constexpr int OFF_O   = OFF_ML + 64;
constexpr int SMEM_ATT = OFF_O + 256;
constexpr int FFN_CHUNK = 64 * FS * 2;
constexpr int NBF = (NST >= 6) ? 4 : 2;
constexpr int FFN_XN = NBF * FFN_CHUNK, FFN_H = FFN_XN + 8192, FFN_RED = FFN_H + 5504, FFN_BAR = FFN_RED + 32768;
constexpr int SMEM_FFN = FFN_BAR + 64;
static_assert(FFN_CHUNK == 43 * DM * 2, "chunk geometry");
constexpr int SMEM_BYTES = SMEM_ATT > SMEM_FFN ? SMEM_ATT : SMEM_FFN;

__device__ __align__(256) uint4 g_q_part[NH * NB * 32];
__device__ __align__(256) uint4 g_attn_part[NB * 32 * NH * 8];
__device__ __align__(256) uint4 g_ffn_part[NB * 32 * N_FFN * 8];
__device__ __align__(256) uint32_t g_progress[64];
#define FK_ONE4 1u, 1u, 1u, 1u
#define FK_ONE16 FK_ONE4, FK_ONE4, FK_ONE4, FK_ONE4
#define FK_ONE64 FK_ONE16, FK_ONE16, FK_ONE16, FK_ONE16
__device__ __align__(256) uint32_t g_epoch[N_CTA] = {FK_ONE64, FK_ONE64, FK_ONE4};

__device__ __forceinline__ uint32_t smem_u32(const void* p) { return (uint32_t)__cvta_generic_to_shared(p); }

__device__ __forceinline__ void mbar_init(uint32_t bar, uint32_t cnt) {
    asm volatile("mbarrier.init.shared::cta.b64 [%0], %1;" :: "r"(bar), "r"(cnt) : "memory");
}
__device__ __forceinline__ void mbar_expect_tx(uint32_t bar, uint32_t bytes) {
    asm volatile("mbarrier.arrive.expect_tx.shared::cta.b64 _, [%0], %1;" :: "r"(bar), "r"(bytes) : "memory");
}
__device__ __forceinline__ uint32_t atom_inc_shared(uint32_t addr) {
    uint32_t old;
    asm volatile("atom.relaxed.cta.shared::cta.add.u32 %0, [%1], 1;" : "=r"(old) : "r"(addr) : "memory");
    return old;
}
__device__ __forceinline__ void mbar_wait(uint32_t bar, uint32_t parity) {
    asm volatile(
        "{\n"
        ".reg .pred p;\n"
        "FK_WAIT:\n"
        "mbarrier.try_wait.parity.shared::cta.b64 p, [%0], %1;\n"
        "@p bra FK_DONE;\n"
        "bra FK_WAIT;\n"
        "FK_DONE:\n"
        "}\n" :: "r"(bar), "r"(parity) : "memory");
}
__device__ __forceinline__ void bulk_load(uint32_t dst, const void* src, uint32_t bytes, uint32_t bar, uint64_t pol) {
    asm volatile("cp.async.bulk.shared::cluster.global.mbarrier::complete_tx::bytes.L2::cache_hint [%0], [%1], %2, [%3], %4;"
                 :: "r"(dst), "l"(src), "r"(bytes), "r"(bar), "l"(pol) : "memory");
}
__device__ __forceinline__ uint4 ldg_nc(const void* p) {
    uint4 v;
    asm volatile("ld.global.nc.L1::no_allocate.v4.u32 {%0,%1,%2,%3}, [%4];"
                 : "=r"(v.x), "=r"(v.y), "=r"(v.z), "=r"(v.w) : "l"(p));
    return v;
}
__device__ __forceinline__ void bulk_load_plain(uint32_t dst, const void* src, uint32_t bytes, uint32_t bar) {
    asm volatile("cp.async.bulk.shared::cluster.global.mbarrier::complete_tx::bytes [%0], [%1], %2, [%3];"
                 :: "r"(dst), "l"(src), "r"(bytes), "r"(bar) : "memory");
}
__device__ __forceinline__ uint32_t ldg_nc32(const void* p) {
    uint32_t v;
    asm volatile("ld.global.nc.L1::no_allocate.u32 %0, [%1];" : "=r"(v) : "l"(p));
    return v;
}
__device__ __forceinline__ uint32_t lds32(uint32_t addr) {
    uint32_t v;
    asm volatile("ld.volatile.shared.u32 %0, [%1];" : "=r"(v) : "r"(addr) : "memory");
    return v;
}
__device__ __forceinline__ uint32_t pin(uint32_t v) {
    uint32_t r;
    asm volatile("mov.b32 %0, %1;" : "=r"(r) : "r"(v));
    return r;
}
__device__ __forceinline__ uint32_t ld_relaxed32(const uint32_t* p) {
    uint32_t v;
    asm volatile("ld.relaxed.gpu.global.u32 %0, [%1];" : "=r"(v) : "l"(p) : "memory");
    return v;
}
__device__ __forceinline__ bool mbar_test(uint32_t bar, uint32_t parity) {
    uint32_t ok;
    asm volatile("{\n.reg .pred p;\nmbarrier.test_wait.parity.shared::cta.b64 p, [%1], %2;\nselp.u32 %0, 1, 0, p;\n}\n"
                 : "=r"(ok) : "r"(bar), "r"(parity) : "memory");
    return ok != 0;
}
__device__ __forceinline__ uint4 ld_relaxed(const uint4* p) {
    uint4 v;
    asm volatile("ld.relaxed.gpu.global.v4.u32 {%0,%1,%2,%3}, [%4];"
                 : "=r"(v.x), "=r"(v.y), "=r"(v.z), "=r"(v.w) : "l"(p) : "memory");
    return v;
}
__device__ __forceinline__ void st_relaxed(uint4* p, uint4 v) {
    asm volatile("st.relaxed.gpu.global.v4.u32 [%0], {%1,%2,%3,%4};"
                 :: "l"(p), "r"(v.x), "r"(v.y), "r"(v.z), "r"(v.w) : "memory");
}
__device__ __forceinline__ void ldsm_x4(uint32_t (&r)[4], uint32_t addr) {
    asm volatile("ldmatrix.sync.aligned.m8n8.x4.shared.b16 {%0,%1,%2,%3}, [%4];"
                 : "=r"(r[0]), "=r"(r[1]), "=r"(r[2]), "=r"(r[3]) : "r"(addr) : "memory");
}
__device__ __forceinline__ void ldsm_x4_t(uint32_t (&r)[4], uint32_t addr) {
    asm volatile("ldmatrix.sync.aligned.m8n8.x4.trans.shared.b16 {%0,%1,%2,%3}, [%4];"
                 : "=r"(r[0]), "=r"(r[1]), "=r"(r[2]), "=r"(r[3]) : "r"(addr) : "memory");
}
__device__ __forceinline__ void mma_bf16(float (&c)[4], const uint32_t (&a)[4], uint32_t b0, uint32_t b1) {
    asm volatile("mma.sync.aligned.m16n8k16.row.col.f32.bf16.bf16.f32 {%0,%1,%2,%3}, {%4,%5,%6,%7}, {%8,%9}, {%0,%1,%2,%3};"
                 : "+f"(c[0]), "+f"(c[1]), "+f"(c[2]), "+f"(c[3])
                 : "r"(a[0]), "r"(a[1]), "r"(a[2]), "r"(a[3]), "r"(b0), "r"(b1));
}
__device__ __forceinline__ float ex2(float x) {
    float r;
    asm("ex2.approx.ftz.f32 %0, %1;" : "=f"(r) : "f"(x));
    return r;
}
__device__ __forceinline__ uint32_t pack_bf16(float lo, float hi) {
    uint32_t r;
    asm("cvt.rn.bf16x2.f32 %0, %1, %2;" : "=r"(r) : "f"(hi), "f"(lo));
    return r;
}
__device__ __forceinline__ float bf_lo(uint32_t w) { return __uint_as_float(w << 16); }
__device__ __forceinline__ float bf_hi(uint32_t w) { return __uint_as_float(w & 0xffff0000u); }
__device__ __forceinline__ float bf16r(float x) { return __bfloat162float(__float2bfloat16_rn(x)); }
__device__ __forceinline__ float silu_f(float x) { return x / (1.0f + __expf(-x)); }

__device__ __forceinline__ void warp_layernorm(const uint4 a, const uint4 b, float (&xn)[16]) {
    float v[16];
    v[0] = bf_lo(a.x); v[1] = bf_hi(a.x); v[2] = bf_lo(a.y); v[3] = bf_hi(a.y);
    v[4] = bf_lo(a.z); v[5] = bf_hi(a.z); v[6] = bf_lo(a.w); v[7] = bf_hi(a.w);
    v[8] = bf_lo(b.x); v[9] = bf_hi(b.x); v[10] = bf_lo(b.y); v[11] = bf_hi(b.y);
    v[12] = bf_lo(b.z); v[13] = bf_hi(b.z); v[14] = bf_lo(b.w); v[15] = bf_hi(b.w);
    float s = 0.f;
#pragma unroll
    for (int i = 0; i < 16; i++) s += v[i];
#pragma unroll
    for (int o = 16; o; o >>= 1) s += __shfl_xor_sync(0xffffffffu, s, o);
    const float mean = s * (1.0f / DM);
    float ss = 0.f;
#pragma unroll
    for (int i = 0; i < 16; i++) { const float d = v[i] - mean; ss = fmaf(d, d, ss); }
#pragma unroll
    for (int o = 16; o; o >>= 1) ss += __shfl_xor_sync(0xffffffffu, ss, o);
    const float m_bf = bf16r(mean);
    const float den = bf16r(sqrtf(bf16r(bf16r(ss * (1.0f / DM)) + 1e-5f)));
#pragma unroll
    for (int i = 0; i < 16; i++) xn[i] = bf16r(__fdiv_rn(bf16r(v[i] - m_bf), den));
}

__device__ __forceinline__ bool ll_valid(const uint4& v, uint32_t tag) { return v.y == tag && v.w == tag; }

__device__ __forceinline__ void ffn_cta(uint8_t* smem, int f, uint32_t tag,
                                        const __nv_bfloat16* __restrict__ x,
                                        const __nv_bfloat16* __restrict__ w1,
                                        const __nv_bfloat16* __restrict__ w2) {
    const int tid = threadIdx.x, warp = tid >> 5, lane = tid & 31;
    const uint32_t sbase = smem_u32(smem), bar = sbase + FFN_BAR;
    float* xnT = reinterpret_cast<float*>(smem + FFN_XN);
    float* hT  = reinterpret_cast<float*>(smem + FFN_H);
    float* red = reinterpret_cast<float*>(smem + FFN_RED);
    if (tid == 0) {
#pragma unroll
        for (int s = 0; s < NBF; s++) mbar_init(bar + s * 8, 1);
    }
    __syncthreads();
    auto issue = [&](int c) {
        const int s = c % NBF;
        if (tid == 0) mbar_expect_tx(bar + s * 8, FFN_CHUNK);
        if (c < 8) {
            __syncthreads();
            if (tid < 64) bulk_load_plain(sbase + s * FFN_CHUNK + tid * (FS * 2), w1 + (size_t)(c * 64 + tid) * FF + f * FS, FS * 2, bar + s * 8);
        } else if (tid == 0) {
            bulk_load_plain(sbase + s * FFN_CHUNK, w2 + (size_t)(f * FS + (c - 8) * 43) * DM, FFN_CHUNK, bar + s * 8);
        }
    };
    for (int c = 0; c < NBF; c++) issue(c);
    if (warp < NB) {
        float xn[16];
        const uint4 xa = ldg_nc(x + warp * DM + lane * 16), xb = ldg_nc(x + warp * DM + lane * 16 + 8);
        warp_layernorm(xa, xb, xn);
#pragma unroll
        for (int i = 0; i < 16; i++) xnT[(lane * 16 + i) * 4 + warp] = xn[i];
    }
    __syncthreads();
    float acc[4][8];
#pragma unroll
    for (int b = 0; b < 4; b++)
#pragma unroll
        for (int c = 0; c < 8; c++) acc[b][c] = 0.f;
#pragma unroll 1
    for (int c = 0; c < 16; c++) {
        const int s = c % NBF;
        mbar_wait(bar + s * 8, (c / NBF) & 1);
        const bool st1 = c < 8;
        const int cg = st1 ? tid % 43 : (tid & 63), r0 = st1 ? tid / 43 : (tid >> 6);
        const int rstep = st1 ? 5 : 4, nrows = st1 ? 64 : 43, rbytes = st1 ? FS * 2 : DM * 2;
        const float* vec = st1 ? xnT + c * 64 * 4 : hT + (c - 8) * 43 * 4;
        const uint8_t* wb = smem + s * FFN_CHUNK + cg * 16;
        if (!st1 || tid < 43 * 5) {
#pragma unroll 2
            for (int k = r0; k < nrows; k += rstep) {
                const uint4 w = *reinterpret_cast<const uint4*>(wb + k * rbytes);
                const float4 xv = *reinterpret_cast<const float4*>(vec + k * 4);
                const float wf[8] = {bf_lo(w.x), bf_hi(w.x), bf_lo(w.y), bf_hi(w.y), bf_lo(w.z), bf_hi(w.z), bf_lo(w.w), bf_hi(w.w)};
#pragma unroll
                for (int j = 0; j < 8; j++) {
                    acc[0][j] = fmaf(xv.x, wf[j], acc[0][j]);
                    acc[1][j] = fmaf(xv.y, wf[j], acc[1][j]);
                    acc[2][j] = fmaf(xv.z, wf[j], acc[2][j]);
                    acc[3][j] = fmaf(xv.w, wf[j], acc[3][j]);
                }
            }
        }
        __syncthreads();
        if (c + NBF < 16) issue(c + NBF);
        if (c == 7) {
            if (tid < 43 * 5) {
#pragma unroll
                for (int b = 0; b < 4; b++)
#pragma unroll
                    for (int j = 0; j < 8; j++) red[(r0 * 4 + b) * FS + cg * 8 + j] = acc[b][j];
            }
#pragma unroll
            for (int b = 0; b < 4; b++)
#pragma unroll
                for (int j = 0; j < 8; j++) acc[b][j] = 0.f;
            __syncthreads();
            for (int i = tid; i < 4 * FS; i += NTHREADS) {
                const int b = i / FS, cc = i % FS;
                float sum = 0.f;
#pragma unroll
                for (int ks = 0; ks < 5; ks++) sum += red[(ks * 4 + b) * FS + cc];
                hT[cc * 4 + b] = bf16r(silu_f(bf16r(sum)));
            }
            __syncthreads();
        }
    }
    {
        const int cg = tid & 63, fs = tid >> 6;
#pragma unroll
        for (int b = 0; b < 4; b++)
#pragma unroll
            for (int j = 0; j < 8; j++) red[(fs * 4 + b) * DM + cg * 8 + j] = acc[b][j];
    }
    __syncthreads();
    for (int i = tid; i < NB * 256; i += NTHREADS) {
        const int b = i >> 8, j = (i >> 3) & 31, p = i & 7;
        float s0 = 0.f, s1 = 0.f;
#pragma unroll
        for (int fs = 0; fs < 4; fs++) { s0 += red[(fs * 4 + b) * DM + 16 * j + p]; s1 += red[(fs * 4 + b) * DM + 16 * j + 8 + p]; }
        st_relaxed(&g_ffn_part[((b * 32 + j) * N_FFN + f) * 8 + p],
                   make_uint4(__float_as_uint(s0), tag, __float_as_uint(s1), tag));
    }
}

__global__ void __launch_bounds__(NTHREADS, 1)
fused_decode_kernel(const __nv_bfloat16* __restrict__ x, const __nv_bfloat16* __restrict__ Kc,
                    const __nv_bfloat16* __restrict__ Vc, const __nv_bfloat16* __restrict__ wq,
                    const __nv_bfloat16* __restrict__ wo, const __nv_bfloat16* __restrict__ w1,
                    const __nv_bfloat16* __restrict__ w2, __nv_bfloat16* __restrict__ out) {
    extern __shared__ __align__(1024) uint8_t smem[];
    const int cta = blockIdx.x;
    const int tid = threadIdx.x, warp = tid >> 5, lane = tid & 31;
    if (cta >= N_ATT) {
        const uint32_t tag = ld_relaxed32(&g_epoch[cta]);
        ffn_cta(smem, cta - N_ATT, tag, x, w1, w2);
        if (tid == 0) { g_epoch[cta] = tag + 1; }
        return;
    }

    const int b = cta & 3, h = cta >> 2;
    const int bh = b * NH + h;
    const uint32_t sbase = pin(smem_u32(smem));
    const uint32_t bar_full = sbase + OFF_BAR;
    const uint32_t cnt_rel = bar_full + NST * 8;
    const char* kp = reinterpret_cast<const char*>(Kc) + (size_t)bh * SK * DH * 2;
    const char* vp = reinterpret_cast<const char*>(Vc) + (size_t)bh * SK * DH * 2;
    const char* wop = reinterpret_cast<const char*>(wo) + (size_t)h * DH * DM * 2;
    uint64_t pol;
    asm volatile("createpolicy.fractional.L2::evict_first.b64 %0, 1.0;" : "=l"(pol));
    auto issue_kv = [&](const char* src, int s) {
        const uint32_t bar = bar_full + s * 8;
        mbar_expect_tx(bar, STAGE_BYTES);
        bulk_load(sbase + s * STAGE_BYTES, src, STAGE_BYTES, bar, pol);
    };
    auto issue_first = [&](int n) { issue_kv(((n & 1) ? vp : kp) + (size_t)(n >> 1) * STAGE_BYTES, n); };
    const uint32_t bar_w = bar_full + 216, cnt_w = bar_full + 224;
    auto issue_w = [&](int q) {
        mbar_expect_tx(bar_w, STAGE_BYTES);
        bulk_load_plain(sbase + OFF_W, wop + (size_t)q * STAGE_BYTES, STAGE_BYTES, bar_w);
    };

    const int g = lane >> 2, t = lane & 3;
    float* xn_s  = reinterpret_cast<float*>(smem + OFF_XN);
    float* red_s = reinterpret_cast<float*>(smem + OFF_RED);
    __nv_bfloat16* q_s = reinterpret_cast<__nv_bfloat16*>(smem + OFF_Q);
    float* ml_s = reinterpret_cast<float*>(smem + OFF_ML);
    __nv_bfloat16* o_s = reinterpret_cast<__nv_bfloat16*>(smem + OFF_O);

    uint4* const q_out = &g_q_part[(h * NB + (lane >> 3)) * 32 + b * 8 + (lane & 7)];
    uint4* const a_out = &g_attn_part[((b * 32 + warp * 4 + t) * NH + h) * 8 + g];

    volatile uint32_t* q_flag = reinterpret_cast<volatile uint32_t*>(smem + OFF_BAR + 192);
    const uint32_t bar_x = bar_full + 200;
    if (tid == 0) {
        mbar_init(bar_full, 1);
        issue_first(0);
        mbar_init(bar_x, 1);
        mbar_expect_tx(bar_x, NB * DM * 2);
        bulk_load_plain(sbase + OFF_X, x, NB * DM * 2, bar_x);
#pragma unroll
        for (int s = 1; s < NST; s++) mbar_init(bar_full + s * 8, 1);
        mbar_init(bar_w, 1);
#pragma unroll
        for (int s = 0; s < NST; s++) *reinterpret_cast<volatile uint32_t*>(smem + OFF_BAR + NST * 8 + s * 4) = 0;
        *reinterpret_cast<volatile uint32_t*>(smem + OFF_BAR + 224) = 0;
        *q_flag = 0;
#pragma unroll 1
        for (int s = 1; s < FK_PRE; s++) issue_first(s);
    }
    uint32_t qf[8][2];
    uint32_t tag;
    {
        uint32_t w[32];
        const __nv_bfloat16* wp = wq + (size_t)(warp * 64 + (lane >> 4) * 32) * (NH * DH) + h * DH + b * 32 + (lane & 15) * 2;
#pragma unroll
        for (int i = 0; i < 32; i++) w[i] = ldg_nc32(wp + (size_t)i * (NH * DH));
        tag = ld_relaxed32(&g_epoch[cta]);
        if (tid == 0) {
#pragma unroll 1
            for (int s = FK_PRE; s < FK_FIRST; s++) issue_first(s);
            asm volatile("prefetch.global.L2 [%0];" :: "l"(wop));
        }
        if (warp == 0) st_relaxed(q_out, make_uint4(0, 0, 0, 0));
        st_relaxed(a_out, make_uint4(0, 0, 0, 0));
        __syncthreads();
        if (warp < 4) {
            float xn[16];
            mbar_wait(bar_x, 0);
            const uint4 xa = *reinterpret_cast<const uint4*>(smem + OFF_X + warp * DM * 2 + lane * 32);
            const uint4 xb = *reinterpret_cast<const uint4*>(smem + OFF_X + warp * DM * 2 + lane * 32 + 16);
            warp_layernorm(xa, xb, xn);
#pragma unroll
            for (int i = 0; i < 16; i += 4)
                *reinterpret_cast<float4*>(xn_s + warp * DM + lane * 16 + i) = make_float4(xn[i], xn[i + 1], xn[i + 2], xn[i + 3]);
        }
        __syncthreads();
        float acc[4][2];
#pragma unroll
        for (int bb = 0; bb < 4; bb++) acc[bb][0] = acc[bb][1] = 0.f;
        const float* xp = xn_s + warp * 64 + (lane >> 4) * 32;
#pragma unroll
        for (int i4 = 0; i4 < 8; i4++) {
#pragma unroll
            for (int bb = 0; bb < 4; bb++) {
                const float4 xv = *reinterpret_cast<const float4*>(xp + bb * DM + i4 * 4);
                const float xs[4] = {xv.x, xv.y, xv.z, xv.w};
#pragma unroll
                for (int u = 0; u < 4; u++) {
                    acc[bb][0] = fmaf(xs[u], bf_lo(w[i4 * 4 + u]), acc[bb][0]);
                    acc[bb][1] = fmaf(xs[u], bf_hi(w[i4 * 4 + u]), acc[bb][1]);
                }
            }
        }
        const bool up = lane >= 16;
        float k0 = up ? acc[2][0] : acc[0][0], k1 = up ? acc[2][1] : acc[0][1];
        float k2 = up ? acc[3][0] : acc[1][0], k3 = up ? acc[3][1] : acc[1][1];
        k0 += __shfl_xor_sync(0xffffffffu, up ? acc[0][0] : acc[2][0], 16);
        k1 += __shfl_xor_sync(0xffffffffu, up ? acc[0][1] : acc[2][1], 16);
        k2 += __shfl_xor_sync(0xffffffffu, up ? acc[1][0] : acc[3][0], 16);
        k3 += __shfl_xor_sync(0xffffffffu, up ? acc[1][1] : acc[3][1], 16);
        float* rp = red_s + warp * 128 + (up ? 64 : 0) + (lane & 15) * 2;
        *reinterpret_cast<float2*>(rp)      = make_float2(k0, k1);
        *reinterpret_cast<float2*>(rp + 32) = make_float2(k2, k3);
        __syncthreads();
        if (warp == 0) {
            float4 s = make_float4(0.f, 0.f, 0.f, 0.f);
#pragma unroll
            for (int w8 = 0; w8 < NCW; w8++) {
                const float4 v = *reinterpret_cast<const float4*>(red_s + w8 * 128 + lane * 4);
                s.x += v.x; s.y += v.y; s.z += v.z; s.w += v.w;
            }
            st_relaxed(q_out, make_uint4(pack_bf16(s.x, s.y), tag, pack_bf16(s.z, s.w), tag));
            const uint4* p = &g_q_part[(h * NB + b) * 32 + lane];
            uint4 v = ld_relaxed(p);
            for (int spin = 0; !ll_valid(v, tag) && spin < (1 << 20); spin++) v = ld_relaxed(p);
            *reinterpret_cast<uint2*>(q_s + lane * 4) = make_uint2(v.x, v.z);
            if (lane == 0) *q_flag = 1;
        }
        if (tid == NTHREADS - 32) {
            int next = FK_FIRST, watch = 0;
            while (next < NST) {
                if (mbar_test(bar_full + watch * 8, 0)) { issue_first(next); next++; watch++; }
                else if (*q_flag) break;
            }
#pragma unroll 1
            for (; next < NST; next++) issue_first(next);
        }
        __syncthreads();
#pragma unroll
        for (int j = 0; j < 8; j++) {
            const int c = (j ^ g) & 7;
            qf[j][0] = *reinterpret_cast<const uint32_t*>(q_s + c * 8 + 2 * t);
            qf[j][1] = *reinterpret_cast<const uint32_t*>(q_s + 64 + c * 8 + 2 * t);
        }
    }

    constexpr float RSQRT_DH = 0.08838834764831845f, LOG2E = 1.4426950408889634f;
    const int li = lane & 7, lm = lane >> 3;
    const uint32_t k_base = pin(sbase + (uint32_t)((warp * 16 + li + 8 * (lm & 1)) * 256 + (lm >> 1) * 128 + li * 16));
    const uint32_t v_base = pin(sbase + (uint32_t)((warp * 16 + li + 8 * (lm >> 1)) * 256 + (lm & 1) * 128 + li * 16));
    const bool diag = (t == (g >> 1));
    uint32_t msk[8];
#pragma unroll
    for (int j = 0; j < 8; j++) msk[j] = pin((j == (g ^ (2 * t)) ? 0x0000ffffu : 0u) | (j == (g ^ (2 * t) ^ 1) ? 0xffff0000u : 0u));
    const uint32_t ones[4] = {0x3f803f80u, 0x3f803f80u, 0x3f803f80u, 0x3f803f80u};

    float acc0[4] = {0.f, 0.f, 0.f, 0.f}, acc1[4] = {0.f, 0.f, 0.f, 0.f}, lacc[4] = {0.f, 0.f, 0.f, 0.f};
    float m_run = -INFINITY, fin_scale = 0.f;
    int st = 0; uint32_t ph = 0;
    int seq = NST;
    uint32_t wa[8][4][4];
    float g0 = 0.f, g1 = 0.f;
    uint4 gv = make_uint4(0, 0, 0, 0);
    const int cp = lane & 7, q4 = lane >> 3;
    const float x0 = __bfloat162float(reinterpret_cast<const __nv_bfloat16*>(smem + OFF_X)[b * DM + h * 16 + cp]);
    const float x1 = __bfloat162float(reinterpret_cast<const __nv_bfloat16*>(smem + OFF_X)[b * DM + h * 16 + 8 + cp]);
    const uint32_t prog_base = (tag - 1) * (uint32_t)(N_ATT * NT);
    const uint32_t prog_s = bar_full + 208;
    uint32_t prog_v = prog_base;
    if (tid == 0) *reinterpret_cast<volatile uint32_t*>(smem + OFF_BAR + 208) = prog_base;
    __syncthreads();
    auto pace = [&](uint32_t pv, uint32_t lim) {
        for (int spin = 0; (int)(pv - lim) < 0 && spin < 4096; spin++) pv = ld_relaxed32(&g_progress[0]);
    };

#pragma unroll 1
    for (int it = 0; it < NT; it++) {
#pragma unroll
        for (int q = 0; q <= 4; q++) {
            if (it == FK_WTILE + q * FK_WSTEP) {
                if (q == 0) {
                    if (tid == 0) {
                        asm volatile("fence.proxy.async.shared::cta;" ::: "memory");
                        issue_w(0);
                    }
                } else {
                    mbar_wait(bar_w, (q - 1) & 1);
                    const uint32_t wb = sbase + OFF_W + (li + 8 * (lane >> 4)) * 1024 + warp * 128 + (lm & 1) * 16;
#pragma unroll
                    for (int j = 0; j < 4; j++) {
                        ldsm_x4_t(wa[2 * q - 2][j], wb + j * 32);
                        ldsm_x4_t(wa[2 * q - 1][j], wb + 16384 + j * 32);
                    }
                    if (q < 4 && lane == 0) {
                        const uint32_t rel = atom_inc_shared(cnt_w);
                        if ((rel & (NCW - 1)) == NCW - 1) issue_w(q);
                    }
                }
                __syncwarp();
            }
        }
        if (it == NT - 12 && warp == 0) {
            gv = ld_relaxed(&g_ffn_part[((b * 32 + h) * N_FFN + q4) * 8 + cp]);
        }
        if (it == NT - 2 && warp == 0) {
            const uint4* p = &g_ffn_part[((b * 32 + h) * N_FFN + q4) * 8 + cp];
            uint4 v = gv;
            for (int spin = 0; !ll_valid(v, tag) && spin < (1 << 20); spin++) { __nanosleep(64); v = ld_relaxed(p); }
            __syncwarp();
            g0 = __uint_as_float(v.x); g1 = __uint_as_float(v.z);
            g0 += __shfl_xor_sync(0xffffffffu, g0, 8);  g1 += __shfl_xor_sync(0xffffffffu, g1, 8);
            g0 += __shfl_xor_sync(0xffffffffu, g0, 16); g1 += __shfl_xor_sync(0xffffffffu, g1, 16);
            g0 = bf16r(silu_f(bf16r(g0))); g1 = bf16r(silu_f(bf16r(g1)));
        }
        if (tid == 0) {
            *reinterpret_cast<volatile uint32_t*>(smem + OFF_BAR + 208) = prog_v;
            prog_v = ld_relaxed32(&g_progress[0]);
        }
        const bool endgame = it >= NT - FK_ENDT;
        const char* k_next = kp + (size_t)(it + NST / 2) * STAGE_BYTES;
        const char* v_next = vp + (size_t)(it + NST / 2) * STAGE_BYTES;
        mbar_wait(bar_full + st * 8, ph);
        float c0[4] = {0.f, 0.f, 0.f, 0.f}, c1[4] = {0.f, 0.f, 0.f, 0.f};
        uint32_t relK = 0, pvK = 0;
        const uint32_t kb = k_base + st * STAGE_BYTES;
        {
#pragma unroll
            for (int j = 0; j < 8; j++) {
                uint32_t a[4];
                ldsm_x4(a, kb ^ (j << 4));
                mma_bf16((j & 1) ? c1 : c0, a, qf[j][0], qf[j][1]);
            }
            if (!endgame && seq < NSEQ && lane == 0) {
                relK = atom_inc_shared(cnt_rel + st * 4);
                pvK = lds32(prog_s);
            }
        }
        float s0 = (g & 1) ? (c0[1] + c1[1]) : (c0[0] + c1[0]);
        float s1 = (g & 1) ? (c0[3] + c1[3]) : (c0[2] + c1[2]);
        {
            const uint32_t r1 = pack_bf16(s0, s1);
            const uint32_t r2 = pack_bf16(bf_lo(r1) * RSQRT_DH, bf_hi(r1) * RSQRT_DH);
            s0 = diag ? bf_lo(r2) : -INFINITY;
            s1 = diag ? bf_hi(r2) : -INFINITY;
        }
        int key = __float_as_int(fmaxf(s0, s1));
        key ^= (key >> 31) & 0x7fffffff;
        key = __reduce_max_sync(0xffffffffu, key);
        key ^= (key >> 31) & 0x7fffffff;
        const float tmax = __int_as_float(key);
        if (tmax > m_run) {
            const float sc = ex2((m_run - tmax) * LOG2E);
#pragma unroll
            for (int i = 0; i < 4; i++) { acc0[i] *= sc; acc1[i] *= sc; }
            lacc[0] *= sc;
            m_run = tmax;
        }
        const float mc = -m_run * LOG2E;
        const uint32_t pk = pack_bf16(ex2(fmaf(s0, LOG2E, mc)), ex2(fmaf(s1, LOG2E, mc)));
        const uint32_t xx = __shfl_sync(0xffffffffu, pk, 9 * t), yy = __shfl_sync(0xffffffffu, pk, 9 * t + 4);
        const uint32_t pp0 = __byte_perm(xx, yy, 0x5410), pp1 = __byte_perm(xx, yy, 0x7632);
        if ((relK & (NCW - 1)) == NCW - 1) {
            pace(pvK, prog_base + (uint32_t)(it * N_ATT - (FK_LEAD)));
            issue_kv(k_next, st);
        }
        __syncwarp();
        const int stK = st;
        seq++;
        if (++st == NST) { st = 0; ph ^= 1; }
        mma_bf16(lacc, ones, pp0, pp1);
        if (it == NT - 1) {
            if (lane == 0) { ml_s[warp] = m_run; ml_s[8 + warp] = lacc[0]; }
            __syncthreads();
            const float4 ma = *reinterpret_cast<const float4*>(ml_s), mb = *reinterpret_cast<const float4*>(ml_s + 4);
            const float4 la = *reinterpret_cast<const float4*>(ml_s + 8), lb = *reinterpret_cast<const float4*>(ml_s + 12);
            const float M = fmaxf(fmaxf(fmaxf(ma.x, ma.y), fmaxf(ma.z, ma.w)), fmaxf(fmaxf(mb.x, mb.y), fmaxf(mb.z, mb.w)));
            const float L = (ex2((ma.x - M) * LOG2E) * la.x + ex2((ma.y - M) * LOG2E) * la.y) + (ex2((ma.z - M) * LOG2E) * la.z + ex2((ma.w - M) * LOG2E) * la.w)
                          + (ex2((mb.x - M) * LOG2E) * lb.x + ex2((mb.y - M) * LOG2E) * lb.y) + (ex2((mb.z - M) * LOG2E) * lb.z + ex2((mb.w - M) * LOG2E) * lb.w);
            fin_scale = __fdividef(ex2((m_run - M) * LOG2E), L);
        }
        mbar_wait(bar_full + st * 8, ph);
        const uint32_t vb = v_base + st * STAGE_BYTES;
        {
            uint32_t relV = 0, pvV = 0;
#pragma unroll
            for (int j = 0; j < 8; j++) {
                uint32_t a[4];
                ldsm_x4_t(a, vb ^ (j << 4));
                mma_bf16((j & 1) ? acc1 : acc0, a, pp0 & msk[j], pp1 & msk[j]);
            }
            if (seq - (endgame ? 1 : 0) < NSEQ && lane == 0) {
                relV = atom_inc_shared(cnt_rel + st * 4);
                pvV = lds32(prog_s);
            }
            if (tid == NTHREADS - 32) asm volatile("red.relaxed.gpu.global.add.u32 [%0], 1;" :: "l"(&g_progress[0]) : "memory");
            if ((relV & (NCW - 1)) == NCW - 1) {
                if (endgame) {
                    pace(pvV, prog_base + (uint32_t)((it + 1) * N_ATT - (FK_LEAD_END)));
                    issue_kv(k_next, stK);
                }
                if (seq < NSEQ) issue_kv(v_next, st);
            }
        }
        __syncwarp();
        seq++;
        if (++st == NST) { st = 0; ph ^= 1; }
    }

    {
        float* o = red_s + warp * 128;
        o[16 * t + g]          = (acc0[0] + acc1[0]) * fin_scale;
        o[16 * t + 8 + g]      = (acc0[1] + acc1[1]) * fin_scale;
        o[64 + 16 * t + g]     = (acc0[2] + acc1[2]) * fin_scale;
        o[64 + 16 * t + 8 + g] = (acc0[3] + acc1[3]) * fin_scale;
    }
    __syncthreads();
    if (tid < DH) {
        float v[8];
#pragma unroll
        for (int w = 0; w < 8; w++) v[w] = red_s[w * 128 + tid];
        const float o = ((v[0] + v[1]) + (v[2] + v[3])) + ((v[4] + v[5]) + (v[6] + v[7]));
        o_s[((tid >> 1) & 3) * 32 + (tid >> 4) * 4 + ((tid >> 3) & 1) * 2 + (tid & 1)] = __float2bfloat16_rn(o);
    }
    __syncthreads();
    {
        float d[4][4];
#pragma unroll
        for (int j = 0; j < 4; j++) { d[j][0] = d[j][1] = d[j][2] = d[j][3] = 0.f; }
        uint4 ov[4];
#pragma unroll
        for (int i = 0; i < 4; i++) ov[i] = *reinterpret_cast<const uint4*>(o_s + t * 32 + i * 8);
#pragma unroll
        for (int i = 0; i < 4; i++) {
#pragma unroll
            for (int j = 0; j < 4; j++) mma_bf16(d[j], wa[2 * i][j], ov[i].x, ov[i].y);
#pragma unroll
            for (int j = 0; j < 4; j++) mma_bf16(d[j], wa[2 * i + 1][j], ov[i].z, ov[i].w);
        }
        float r0 = d[0][0], r1 = d[0][2];
        if (t == 1) { r0 = d[1][0]; r1 = d[1][2]; }
        if (t == 2) { r0 = d[2][0]; r1 = d[2][2]; }
        if (t == 3) { r0 = d[3][0]; r1 = d[3][2]; }
        st_relaxed(a_out, make_uint4(__float_as_uint(r0), tag, __float_as_uint(r1), tag));
    }
    if (warp == 0) {
        const uint4* p = &g_attn_part[((b * 32 + h) * NH + q4 * 8) * 8 + cp];
        uint4 v[8];
#pragma unroll
        for (int i = 0; i < 8; i++) v[i] = ld_relaxed(p + i * 8);
        for (int spin = 0; spin < (1 << 20); spin++) {
            bool ok = true;
#pragma unroll
            for (int i = 0; i < 8; i++) {
                if (!ll_valid(v[i], tag)) { v[i] = ld_relaxed(p + i * 8); ok = false; }
            }
            if (ok) break;
        }
        __syncwarp();
        float s0 = ((__uint_as_float(v[0].x) + __uint_as_float(v[1].x)) + (__uint_as_float(v[2].x) + __uint_as_float(v[3].x)))
                 + ((__uint_as_float(v[4].x) + __uint_as_float(v[5].x)) + (__uint_as_float(v[6].x) + __uint_as_float(v[7].x)));
        float s1 = ((__uint_as_float(v[0].z) + __uint_as_float(v[1].z)) + (__uint_as_float(v[2].z) + __uint_as_float(v[3].z)))
                 + ((__uint_as_float(v[4].z) + __uint_as_float(v[5].z)) + (__uint_as_float(v[6].z) + __uint_as_float(v[7].z)));
        s0 += __shfl_xor_sync(0xffffffffu, s0, 8);  s1 += __shfl_xor_sync(0xffffffffu, s1, 8);
        s0 += __shfl_xor_sync(0xffffffffu, s0, 16); s1 += __shfl_xor_sync(0xffffffffu, s1, 16);
        if (lane < 8) {
            out[b * DM + h * 16 + cp]     = __float2bfloat16_rn(x0 + bf16r(bf16r(s0) * g0));
            out[b * DM + h * 16 + 8 + cp] = __float2bfloat16_rn(x1 + bf16r(bf16r(s1) * g1));
        }
        if (lane == 0) { g_epoch[cta] = tag + 1; }
    }
}

}

extern "C" void kernel_launch(void* const* d_in, const int* in_sizes, int n_in, void* d_out, int out_size) {
    (void)in_sizes; (void)n_in; (void)out_size;
    const __nv_bfloat16* x  = (const __nv_bfloat16*)d_in[0];
    const __nv_bfloat16* Kc = (const __nv_bfloat16*)d_in[1];
    const __nv_bfloat16* Vc = (const __nv_bfloat16*)d_in[2];
    const __nv_bfloat16* wq = (const __nv_bfloat16*)d_in[3];
    const __nv_bfloat16* wo = (const __nv_bfloat16*)d_in[4];
    const __nv_bfloat16* w1 = (const __nv_bfloat16*)d_in[6];
    const __nv_bfloat16* w2 = (const __nv_bfloat16*)d_in[7];

    static bool attr_set = false;
    if (!attr_set) {
        cudaFuncSetAttribute(fk::fused_decode_kernel, cudaFuncAttributeMaxDynamicSharedMemorySize, fk::SMEM_BYTES);
        attr_set = true;
    }
    fk::fused_decode_kernel<<<fk::N_CTA, fk::NTHREADS, fk::SMEM_BYTES>>>(x, Kc, Vc, wq, wo, w1, w2, (__nv_bfloat16*)d_out);
}
```

```cpp
#include <cuda_runtime.h>
#include <cuda_bf16.h>
#include <stdint.h>

namespace fk {

#define FK_NST 4
#define FK_FIRST 2
#define FK_PRE 1
#define FK_WTILE 4
#define FK_WSTEP 10
#define FK_LEAD 0
#define FK_ENDT 16
#define FK_LEAD_END 40

constexpr int NB = 4, NH = 32, SK = 8192, DH = 128, DM = 512, FF = 1376;
constexpr int TK = 128;
constexpr int NT = SK / TK;
constexpr int STAGE_BYTES = TK * DH * 2;
constexpr int NST = FK_NST;
constexpr int NCW = 8;
constexpr int NTHREADS = NCW * 32;
constexpr int N_ATT = NB * NH;
constexpr int N_FFN = 4;
constexpr int FS = FF / N_FFN;
constexpr int N_CTA = N_ATT + N_FFN;
constexpr int NSEQ = 2 * NT;
static_assert(NST % 2 == 0, "K tiles live in the even stages, V tiles in the odd ones");

constexpr int OFF_W   = NST * STAGE_BYTES;
constexpr int OFF_XN  = OFF_W;
constexpr int OFF_X   = OFF_W + 8192;
constexpr int OFF_RED = OFF_W + 12288;
constexpr int OFF_BAR = OFF_W + STAGE_BYTES;
constexpr int OFF_Q   = OFF_BAR + 256;
constexpr int OFF_ML  = OFF_Q + 256;
constexpr int OFF_O   = OFF_ML + 64;
constexpr int SMEM_ATT = OFF_O + 256;
constexpr int FFN_CHUNK = 64 * FS * 2;
constexpr int NBF = (NST >= 6) ? 4 : 2;
constexpr int FFN_XN = NBF * FFN_CHUNK, FFN_H = FFN_XN + 8192, FFN_RED = FFN_H + 5504, FFN_BAR = FFN_RED + 32768;
constexpr int SMEM_FFN = FFN_BAR + 64;
static_assert(FFN_CHUNK == 43 * DM * 2, "chunk geometry");
constexpr int SMEM_BYTES = SMEM_ATT > SMEM_FFN ? SMEM_ATT : SMEM_FFN;

__device__ __align__(256) uint4 g_q_part[NH * NB * 32];
__device__ __align__(256) uint4 g_attn_part[NB * 32 * NH * 8];
__device__ __align__(256) uint4 g_ffn_part[NB * 32 * N_FFN * 8];
__device__ __align__(256) uint32_t g_progress[64];
#define FK_ONE4 1u, 1u, 1u, 1u
#define FK_ONE16 FK_ONE4, FK_ONE4, FK_ONE4, FK_ONE4
#define FK_ONE64 FK_ONE16, FK_ONE16, FK_ONE16, FK_ONE16
__device__ __align__(256) uint32_t g_epoch[N_CTA] = {FK_ONE64, FK_ONE64, FK_ONE4};

__device__ __forceinline__ uint32_t smem_u32(const void* p) { return (uint32_t)__cvta_generic_to_shared(p); }

__device__ __forceinline__ void mbar_init(uint32_t bar, uint32_t cnt) {
    asm volatile("mbarrier.init.shared::cta.b64 [%0], %1;" :: "r"(bar), "r"(cnt) : "memory");
}
__device__ __forceinline__ void mbar_expect_tx(uint32_t bar, uint32_t bytes) {
    asm volatile("mbarrier.arrive.expect_tx.shared::cta.b64 _, [%0], %1;" :: "r"(bar), "r"(bytes) : "memory");
}
__device__ __forceinline__ uint32_t atom_inc_shared(uint32_t addr) {
    uint32_t old;
    asm volatile("atom.relaxed.cta.shared::cta.add.u32 %0, [%1], 1;" : "=r"(old) : "r"(addr) : "memory");
    return old;
}
__device__ __forceinline__ void mbar_wait(uint32_t bar, uint32_t parity) {
    asm volatile(
        "{\n"
        ".reg .pred p;\n"
        "FK_WAIT:\n"
        "mbarrier.try_wait.parity.shared::cta.b64 p, [%0], %1;\n"
        "@p bra FK_DONE;\n"
        "bra FK_WAIT;\n"
        "FK_DONE:\n"
        "}\n" :: "r"(bar), "r"(parity) : "memory");
}
__device__ __forceinline__ void bulk_load(uint32_t dst, const void* src, uint32_t bytes, uint32_t bar, uint64_t pol) {
    asm volatile("cp.async.bulk.shared::cluster.global.mbarrier::complete_tx::bytes.L2::cache_hint [%0], [%1], %2, [%3], %4;"
                 :: "r"(dst), "l"(src), "r"(bytes), "r"(bar), "l"(pol) : "memory");
}
__device__ __forceinline__ uint4 ldg_nc(const void* p) {
    uint4 v;
    asm volatile("ld.global.nc.L1::no_allocate.v4.u32 {%0,%1,%2,%3}, [%4];"
                 : "=r"(v.x), "=r"(v.y), "=r"(v.z), "=r"(v.w) : "l"(p));
    return v;
}
__device__ __forceinline__ void bulk_load_plain(uint32_t dst, const void* src, uint32_t bytes, uint32_t bar) {
    asm volatile("cp.async.bulk.shared::cluster.global.mbarrier::complete_tx::bytes [%0], [%1], %2, [%3];"
                 :: "r"(dst), "l"(src), "r"(bytes), "r"(bar) : "memory");
}
__device__ __forceinline__ uint32_t ldg_nc32(const void* p) {
    uint32_t v;
    asm volatile("ld.global.nc.L1::no_allocate.u32 %0, [%1];" : "=r"(v) : "l"(p));
    return v;
}
__device__ __forceinline__ uint32_t lds32(uint32_t addr) {
    uint32_t v;
    asm volatile("ld.volatile.shared.u32 %0, [%1];" : "=r"(v) : "r"(addr) : "memory");
    return v;
}
__device__ __forceinline__ uint32_t pin(uint32_t v) {
    uint32_t r;
    asm volatile("mov.b32 %0, %1;" : "=r"(r) : "r"(v));
    return r;
}
__device__ __forceinline__ uint32_t ld_relaxed32(const uint32_t* p) {
    uint32_t v;
    asm volatile("ld.relaxed.gpu.global.u32 %0, [%1];" : "=r"(v) : "l"(p) : "memory");
    return v;
}
__device__ __forceinline__ bool mbar_test(uint32_t bar, uint32_t parity) {
    uint32_t ok;
    asm volatile("{\n.reg .pred p;\nmbarrier.test_wait.parity.shared::cta.b64 p, [%1], %2;\nselp.u32 %0, 1, 0, p;\n}\n"
                 : "=r"(ok) : "r"(bar), "r"(parity) : "memory");
    return ok != 0;
}
__device__ __forceinline__ uint4 ld_relaxed(const uint4* p) {
    uint4 v;
    asm volatile("ld.relaxed.gpu.global.v4.u32 {%0,%1,%2,%3}, [%4];"
                 : "=r"(v.x), "=r"(v.y), "=r"(v.z), "=r"(v.w) : "l"(p) : "memory");
    return v;
}
__device__ __forceinline__ void st_relaxed(uint4* p, uint4 v) {
    asm volatile("st.relaxed.gpu.global.v4.u32 [%0], {%1,%2,%3,%4};"
                 :: "l"(p), "r"(v.x), "r"(v.y), "r"(v.z), "r"(v.w) : "memory");
}
__device__ __forceinline__ void ldsm_x4(uint32_t (&r)[4], uint32_t addr) {
    asm volatile("ldmatrix.sync.aligned.m8n8.x4.shared.b16 {%0,%1,%2,%3}, [%4];"
                 : "=r"(r[0]), "=r"(r[1]), "=r"(r[2]), "=r"(r[3]) : "r"(addr) : "memory");
}
__device__ __forceinline__ void ldsm_x4_t(uint32_t (&r)[4], uint32_t addr) {
    asm volatile("ldmatrix.sync.aligned.m8n8.x4.trans.shared.b16 {%0,%1,%2,%3}, [%4];"
                 : "=r"(r[0]), "=r"(r[1]), "=r"(r[2]), "=r"(r[3]) : "r"(addr) : "memory");
}
__device__ __forceinline__ void mma_bf16(float (&c)[4], const uint32_t (&a)[4], uint32_t b0, uint32_t b1) {
    asm volatile("mma.sync.aligned.m16n8k16.row.col.f32.bf16.bf16.f32 {%0,%1,%2,%3}, {%4,%5,%6,%7}, {%8,%9}, {%0,%1,%2,%3};"
                 : "+f"(c[0]), "+f"(c[1]), "+f"(c[2]), "+f"(c[3])
                 : "r"(a[0]), "r"(a[1]), "r"(a[2]), "r"(a[3]), "r"(b0), "r"(b1));
}
__device__ __forceinline__ float ex2(float x) {
    float r;
    asm("ex2.approx.ftz.f32 %0, %1;" : "=f"(r) : "f"(x));
    return r;
}
__device__ __forceinline__ uint32_t pack_bf16(float lo, float hi) {
    uint32_t r;
    asm("cvt.rn.bf16x2.f32 %0, %1, %2;" : "=r"(r) : "f"(hi), "f"(lo));
    return r;
}
__device__ __forceinline__ float bf_lo(uint32_t w) { return __uint_as_float(w << 16); }
__device__ __forceinline__ float bf_hi(uint32_t w) { return __uint_as_float(w & 0xffff0000u); }
__device__ __forceinline__ float bf16r(float x) { return __bfloat162float(__float2bfloat16_rn(x)); }
__device__ __forceinline__ float silu_f(float x) { return x / (1.0f + __expf(-x)); }

__device__ __forceinline__ void warp_layernorm(const uint4 a, const uint4 b, float (&xn)[16]) {
    float v[16];
    v[0] = bf_lo(a.x); v[1] = bf_hi(a.x); v[2] = bf_lo(a.y); v[3] = bf_hi(a.y);
    v[4] = bf_lo(a.z); v[5] = bf_hi(a.z); v[6] = bf_lo(a.w); v[7] = bf_hi(a.w);
    v[8] = bf_lo(b.x); v[9] = bf_hi(b.x); v[10] = bf_lo(b.y); v[11] = bf_hi(b.y);
    v[12] = bf_lo(b.z); v[13] = bf_hi(b.z); v[14] = bf_lo(b.w); v[15] = bf_hi(b.w);
    float s = 0.f;
#pragma unroll
    for (int i = 0; i < 16; i++) s += v[i];
#pragma unroll
    for (int o = 16; o; o >>= 1) s += __shfl_xor_sync(0xffffffffu, s, o);
    const float mean = s * (1.0f / DM);
    float ss = 0.f;
#pragma unroll
    for (int i = 0; i < 16; i++) { const float d = v[i] - mean; ss = fmaf(d, d, ss); }
#pragma unroll
    for (int o = 16; o; o >>= 1) ss += __shfl_xor_sync(0xffffffffu, ss, o);
    const float m_bf = bf16r(mean);
    const float den = bf16r(sqrtf(bf16r(bf16r(ss * (1.0f / DM)) + 1e-5f)));
#pragma unroll
    for (int i = 0; i < 16; i++) xn[i] = bf16r(__fdiv_rn(bf16r(v[i] - m_bf), den));
}

__device__ __forceinline__ bool ll_valid(const uint4& v, uint32_t tag) { return v.y == tag && v.w == tag; }

__device__ __forceinline__ void ffn_cta(uint8_t* smem, int f, uint32_t tag,
                                        const __nv_bfloat16* __restrict__ x,
                                        const __nv_bfloat16* __restrict__ w1,
                                        const __nv_bfloat16* __restrict__ w2) {
    const int tid = threadIdx.x, warp = tid >> 5, lane = tid & 31;
    const uint32_t sbase = smem_u32(smem), bar = sbase + FFN_BAR;
    float* xnT = reinterpret_cast<float*>(smem + FFN_XN);
    float* hT  = reinterpret_cast<float*>(smem + FFN_H);
    float* red = reinterpret_cast<float*>(smem + FFN_RED);
    if (tid == 0) {
#pragma unroll
        for (int s = 0; s < NBF; s++) mbar_init(bar + s * 8, 1);
    }
    __syncthreads();
    auto issue = [&](int c) {
        const int s = c % NBF;
        if (tid == 0) mbar_expect_tx(bar + s * 8, FFN_CHUNK);
        if (c < 8) {
            __syncthreads();
            if (tid < 64) bulk_load_plain(sbase + s * FFN_CHUNK + tid * (FS * 2), w1 + (size_t)(c * 64 + tid) * FF + f * FS, FS * 2, bar + s * 8);
        } else if (tid == 0) {
            bulk_load_plain(sbase + s * FFN_CHUNK, w2 + (size_t)(f * FS + (c - 8) * 43) * DM, FFN_CHUNK, bar + s * 8);
        }
    };
    for (int c = 0; c < NBF; c++) issue(c);
    if (warp < NB) {
        float xn[16];
        const uint4 xa = ldg_nc(x + warp * DM + lane * 16), xb = ldg_nc(x + warp * DM + lane * 16 + 8);
        warp_layernorm(xa, xb, xn);
#pragma unroll
        for (int i = 0; i < 16; i++) xnT[(lane * 16 + i) * 4 + warp] = xn[i];
    }
    __syncthreads();
    float acc[4][8];
#pragma unroll
    for (int b = 0; b < 4; b++)
#pragma unroll
        for (int c = 0; c < 8; c++) acc[b][c] = 0.f;
#pragma unroll 1
    for (int c = 0; c < 16; c++) {
        const int s = c % NBF;
        mbar_wait(bar + s * 8, (c / NBF) & 1);
        const bool st1 = c < 8;
        const int cg = st1 ? tid % 43 : (tid & 63), r0 = st1 ? tid / 43 : (tid >> 6);
        const int rstep = st1 ? 5 : 4, nrows = st1 ? 64 : 43, rbytes = st1 ? FS * 2 : DM * 2;
        const float* vec = st1 ? xnT + c * 64 * 4 : hT + (c - 8) * 43 * 4;
        const uint8_t* wb = smem + s * FFN_CHUNK + cg * 16;
        if (!st1 || tid < 43 * 5) {
#pragma unroll 2
            for (int k = r0; k < nrows; k += rstep) {
                const uint4 w = *reinterpret_cast<const uint4*>(wb + k * rbytes);
                const float4 xv = *reinterpret_cast<const float4*>(vec + k * 4);
                const float wf[8] = {bf_lo(w.x), bf_hi(w.x), bf_lo(w.y), bf_hi(w.y), bf_lo(w.z), bf_hi(w.z), bf_lo(w.w), bf_hi(w.w)};
#pragma unroll
                for (int j = 0; j < 8; j++) {
                    acc[0][j] = fmaf(xv.x, wf[j], acc[0][j]);
                    acc[1][j] = fmaf(xv.y, wf[j], acc[1][j]);
                    acc[2][j] = fmaf(xv.z, wf[j], acc[2][j]);
                    acc[3][j] = fmaf(xv.w, wf[j], acc[3][j]);
                }
            }
        }
        __syncthreads();
        if (c + NBF < 16) issue(c + NBF);
        if (c == 7) {
            if (tid < 43 * 5) {
#pragma unroll
                for (int b = 0; b < 4; b++)
#pragma unroll
                    for (int j = 0; j < 8; j++) red[(r0 * 4 + b) * FS + cg * 8 + j] = acc[b][j];
            }
#pragma unroll
            for (int b = 0; b < 4; b++)
#pragma unroll
                for (int j = 0; j < 8; j++) acc[b][j] = 0.f;
            __syncthreads();
            for (int i = tid; i < 4 * FS; i += NTHREADS) {
                const int b = i / FS, cc = i % FS;
                float sum = 0.f;
#pragma unroll
                for (int ks = 0; ks < 5; ks++) sum += red[(ks * 4 + b) * FS + cc];
                hT[cc * 4 + b] = bf16r(silu_f(bf16r(sum)));
            }
            __syncthreads();
        }
    }
    {
        const int cg = tid & 63, fs = tid >> 6;
#pragma unroll
        for (int b = 0; b < 4; b++)
#pragma unroll
            for (int j = 0; j < 8; j++) red[(fs * 4 + b) * DM + cg * 8 + j] = acc[b][j];
    }
    __syncthreads();
    for (int i = tid; i < NB * 256; i += NTHREADS) {
        const int b = i >> 8, j = (i >> 3) & 31, p = i & 7;
        float s0 = 0.f, s1 = 0.f;
#pragma unroll
        for (int fs = 0; fs < 4; fs++) { s0 += red[(fs * 4 + b) * DM + 16 * j + p]; s1 += red[(fs * 4 + b) * DM + 16 * j + 8 + p]; }
        st_relaxed(&g_ffn_part[((b * 32 + j) * N_FFN + f) * 8 + p],
                   make_uint4(__float_as_uint(s0), tag, __float_as_uint(s1), tag));
    }
}

__global__ void __launch_bounds__(NTHREADS, 1)
fused_decode_kernel(const __nv_bfloat16* __restrict__ x, const __nv_bfloat16* __restrict__ Kc,
                    const __nv_bfloat16* __restrict__ Vc, const __nv_bfloat16* __restrict__ wq,
                    const __nv_bfloat16* __restrict__ wo, const __nv_bfloat16* __restrict__ w1,
                    const __nv_bfloat16* __restrict__ w2, __nv_bfloat16* __restrict__ out) {
    extern __shared__ __align__(1024) uint8_t smem[];
    const int cta = blockIdx.x;
    const int tid = threadIdx.x, warp = tid >> 5, lane = tid & 31;
    if (cta >= N_ATT) {
        const uint32_t tag = ld_relaxed32(&g_epoch[cta]);
        ffn_cta(smem, cta - N_ATT, tag, x, w1, w2);
        if (tid == 0) { g_epoch[cta] = tag + 1; }
        return;
    }

    const int b = cta & 3, h = cta >> 2;
    const int bh = b * NH + h;
    const uint32_t sbase = pin(smem_u32(smem));
    const uint32_t bar_full = sbase + OFF_BAR;
    const uint32_t cnt_rel = bar_full + NST * 8;
    const char* kp = reinterpret_cast<const char*>(Kc) + (size_t)bh * SK * DH * 2;
    const char* vp = reinterpret_cast<const char*>(Vc) + (size_t)bh * SK * DH * 2;
    const char* wop = reinterpret_cast<const char*>(wo) + (size_t)h * DH * DM * 2;
    uint64_t pol;
    asm volatile("createpolicy.fractional.L2::evict_first.b64 %0, 1.0;" : "=l"(pol));
    auto issue_kv = [&](const char* src, int s) {
        const uint32_t bar = bar_full + s * 8;
        mbar_expect_tx(bar, STAGE_BYTES);
        bulk_load(sbase + s * STAGE_BYTES, src, STAGE_BYTES, bar, pol);
    };
    auto issue_first = [&](int n) { issue_kv(((n & 1) ? vp : kp) + (size_t)(n >> 1) * STAGE_BYTES, n); };
    const uint32_t bar_w = bar_full + 216, cnt_w = bar_full + 224;
    auto issue_w = [&](int q) {
        mbar_expect_tx(bar_w, STAGE_BYTES);
        bulk_load_plain(sbase + OFF_W, wop + (size_t)q * STAGE_BYTES, STAGE_BYTES, bar_w);
    };

    const int g = lane >> 2, t = lane & 3;
    float* xn_s  = reinterpret_cast<float*>(smem + OFF_XN);
    float* red_s = reinterpret_cast<float*>(smem + OFF_RED);
    __nv_bfloat16* q_s = reinterpret_cast<__nv_bfloat16*>(smem + OFF_Q);
    float* ml_s = reinterpret_cast<float*>(smem + OFF_ML);
    __nv_bfloat16* o_s = reinterpret_cast<__nv_bfloat16*>(smem + OFF_O);

    uint4* const q_out = &g_q_part[(h * NB + (lane >> 3)) * 32 + b * 8 + (lane & 7)];
    uint4* const a_out = &g_attn_part[((b * 32 + warp * 4 + t) * NH + h) * 8 + g];

    volatile uint32_t* q_flag = reinterpret_cast<volatile uint32_t*>(smem + OFF_BAR + 192);
    const uint32_t bar_x = bar_full + 200;
    if (tid == 0) {
        mbar_init(bar_full, 1);
        issue_first(0);
        mbar_init(bar_x, 1);
        mbar_expect_tx(bar_x, NB * DM * 2);
        bulk_load_plain(sbase + OFF_X, x, NB * DM * 2, bar_x);
#pragma unroll
        for (int s = 1; s < NST; s++) mbar_init(bar_full + s * 8, 1);
        mbar_init(bar_w, 1);
#pragma unroll
        for (int s = 0; s < NST; s++) *reinterpret_cast<volatile uint32_t*>(smem + OFF_BAR + NST * 8 + s * 4) = 0;
        *reinterpret_cast<volatile uint32_t*>(smem + OFF_BAR + 224) = 0;
        *q_flag = 0;
#pragma unroll 1
        for (int s = 1; s < FK_PRE; s++) issue_first(s);
    }
    uint32_t qf[8][2];
    uint32_t tag;
    {
        uint32_t w[32];
        const __nv_bfloat16* wp = wq + (size_t)(warp * 64 + (lane >> 4) * 32) * (NH * DH) + h * DH + b * 32 + (lane & 15) * 2;
#pragma unroll
        for (int i = 0; i < 32; i++) w[i] = ldg_nc32(wp + (size_t)i * (NH * DH));
        tag = ld_relaxed32(&g_epoch[cta]);
        if (tid == 0) {
#pragma unroll 1
            for (int s = FK_PRE; s < FK_FIRST; s++) issue_first(s);
            asm volatile("prefetch.global.L2 [%0];" :: "l"(wop));
        }
        if (warp == 0) st_relaxed(q_out, make_uint4(0, 0, 0, 0));
        st_relaxed(a_out, make_uint4(0, 0, 0, 0));
        __syncthreads();
        if (warp < 4) {
            float xn[16];
            mbar_wait(bar_x, 0);
            const uint4 xa = *reinterpret_cast<const uint4*>(smem + OFF_X + warp * DM * 2 + lane * 32);
            const uint4 xb = *reinterpret_cast<const uint4*>(smem + OFF_X + warp * DM * 2 + lane * 32 + 16);
            warp_layernorm(xa, xb, xn);
#pragma unroll
            for (int i = 0; i < 16; i += 4)
                *reinterpret_cast<float4*>(xn_s + warp * DM + lane * 16 + i) = make_float4(xn[i], xn[i + 1], xn[i + 2], xn[i + 3]);
        }
        __syncthreads();
        float acc[4][2];
#pragma unroll
        for (int bb = 0; bb < 4; bb++) acc[bb][0] = acc[bb][1] = 0.f;
        const float* xp = xn_s + warp * 64 + (lane >> 4) * 32;
#pragma unroll
        for (int i4 = 0; i4 < 8; i4++) {
#pragma unroll
            for (int bb = 0; bb < 4; bb++) {
                const float4 xv = *reinterpret_cast<const float4*>(xp + bb * DM + i4 * 4);
                const float xs[4] = {xv.x, xv.y, xv.z, xv.w};
#pragma unroll
                for (int u = 0; u < 4; u++) {
                    acc[bb][0] = fmaf(xs[u], bf_lo(w[i4 * 4 + u]), acc[bb][0]);
                    acc[bb][1] = fmaf(xs[u], bf_hi(w[i4 * 4 + u]), acc[bb][1]);
                }
            }
        }
        const bool up = lane >= 16;
        float k0 = up ? acc[2][0] : acc[0][0], k1 = up ? acc[2][1] : acc[0][1];
        float k2 = up ? acc[3][0] : acc[1][0], k3 = up ? acc[3][1] : acc[1][1];
        k0 += __shfl_xor_sync(0xffffffffu, up ? acc[0][0] : acc[2][0], 16);
        k1 += __shfl_xor_sync(0xffffffffu, up ? acc[0][1] : acc[2][1], 16);
        k2 += __shfl_xor_sync(0xffffffffu, up ? acc[1][0] : acc[3][0], 16);
        k3 += __shfl_xor_sync(0xffffffffu, up ? acc[1][1] : acc[3][1], 16);
        float* rp = red_s + warp * 128 + (up ? 64 : 0) + (lane & 15) * 2;
        *reinterpret_cast<float2*>(rp)      = make_float2(k0, k1);
        *reinterpret_cast<float2*>(rp + 32) = make_float2(k2, k3);
        __syncthreads();
        if (warp == 0) {
            float4 s = make_float4(0.f, 0.f, 0.f, 0.f);
#pragma unroll
            for (int w8 = 0; w8 < NCW; w8++) {
                const float4 v = *reinterpret_cast<const float4*>(red_s + w8 * 128 + lane * 4);
                s.x += v.x; s.y += v.y; s.z += v.z; s.w += v.w;
            }
            st_relaxed(q_out, make_uint4(pack_bf16(s.x, s.y), tag, pack_bf16(s.z, s.w), tag));
            const uint4* p = &g_q_part[(h * NB + b) * 32 + lane];
            uint4 v = ld_relaxed(p);
            for (int spin = 0; !ll_valid(v, tag) && spin < (1 << 20); spin++) v = ld_relaxed(p);
            *reinterpret_cast<uint2*>(q_s + lane * 4) = make_uint2(v.x, v.z);
            if (lane == 0) *q_flag = 1;
        }
        if (tid == NTHREADS - 32) {
            int next = FK_FIRST, watch = 0;
            while (next < NST) {
                if (mbar_test(bar_full + watch * 8, 0)) { issue_first(next); next++; watch++; }
                else if (*q_flag) break;
            }
#pragma unroll 1
            for (; next < NST; next++) issue_first(next);
        }
        __syncthreads();
#pragma unroll
        for (int j = 0; j < 8; j++) {
            const int c = (j ^ g) & 7;
            qf[j][0] = *reinterpret_cast<const uint32_t*>(q_s + c * 8 + 2 * t);
            qf[j][1] = *reinterpret_cast<const uint32_t*>(q_s + 64 + c * 8 + 2 * t);
        }
    }

    constexpr float RSQRT_DH = 0.08838834764831845f, LOG2E = 1.4426950408889634f;
    const int li = lane & 7, lm = lane >> 3;
    const uint32_t k_base = pin(sbase + (uint32_t)((warp * 16 + li + 8 * (lm & 1)) * 256 + (lm >> 1) * 128 + li * 16));
    const uint32_t v_base = pin(sbase + (uint32_t)((warp * 16 + li + 8 * (lm >> 1)) * 256 + (lm & 1) * 128 + li * 16));
    const bool diag = (t == (g >> 1));
    uint32_t msk[8];
#pragma unroll
    for (int j = 0; j < 8; j++) msk[j] = pin((j == (g ^ (2 * t)) ? 0x0000ffffu : 0u) | (j == (g ^ (2 * t) ^ 1) ? 0xffff0000u : 0u));
    const uint32_t ones[4] = {0x3f803f80u, 0x3f803f80u, 0x3f803f80u, 0x3f803f80u};

    float acc0[4] = {0.f, 0.f, 0.f, 0.f}, acc1[4] = {0.f, 0.f, 0.f, 0.f}, lacc[4] = {0.f, 0.f, 0.f, 0.f};
    float m_raw = -INFINITY;
    float m_run = -INFINITY, mc = 0.f;
    float fin_scale = 0.f;
    int st = 0; uint32_t ph = 0;
    int seq = NST;
    uint32_t wa[8][4][4];
    float g0 = 0.f, g1 = 0.f;
    uint4 gv = make_uint4(0, 0, 0, 0);
    const int cp = lane & 7, q4 = lane >> 3;
    const float x0 = __bfloat162float(reinterpret_cast<const __nv_bfloat16*>(smem + OFF_X)[b * DM + h * 16 + cp]);
    const float x1 = __bfloat162float(reinterpret_cast<const __nv_bfloat16*>(smem + OFF_X)[b * DM + h * 16 + 8 + cp]);
    const uint32_t prog_base = (tag - 1) * (uint32_t)(N_ATT * NT);
    const uint32_t prog_s = bar_full + 208;
    uint32_t prog_v = prog_base;
    if (tid == 0) *reinterpret_cast<volatile uint32_t*>(smem + OFF_BAR + 208) = prog_base;
    __syncthreads();
    auto pace = [&](uint32_t pv, uint32_t lim) {
        for (int spin = 0; (int)(pv - lim) < 0 && spin < 4096; spin++) pv = ld_relaxed32(&g_progress[0]);
    };

#pragma unroll 1
    for (int it = 0; it < NT; it++) {
#pragma unroll
        for (int q = 0; q <= 4; q++) {
            if (it == FK_WTILE + q * FK_WSTEP) {
                if (q == 0) {
                    if (tid == 0) {
                        asm volatile("fence.proxy.async.shared::cta;" ::: "memory");
                        issue_w(0);
                    }
                } else {
                    mbar_wait(bar_w, (q - 1) & 1);
                    const uint32_t wb = sbase + OFF_W + (li + 8 * (lane >> 4)) * 1024 + warp * 128 + (lm & 1) * 16;
#pragma unroll
                    for (int j = 0; j < 4; j++) {
                        ldsm_x4_t(wa[2 * q - 2][j], wb + j * 32);
                        ldsm_x4_t(wa[2 * q - 1][j], wb + 16384 + j * 32);
                    }
                    if (q < 4 && lane == 0) {
                        const uint32_t rel = atom_inc_shared(cnt_w);
                        if ((rel & (NCW - 1)) == NCW - 1) issue_w(q);
                    }
                }
                __syncwarp();
            }
        }
        if (it == NT - 12 && warp == 0) {
            gv = ld_relaxed(&g_ffn_part[((b * 32 + h) * N_FFN + q4) * 8 + cp]);
        }
        if (it == NT - 2 && warp == 0) {
            const uint4* p = &g_ffn_part[((b * 32 + h) * N_FFN + q4) * 8 + cp];
            uint4 v = gv;
            for (int spin = 0; !ll_valid(v, tag) && spin < (1 << 20); spin++) { __nanosleep(64); v = ld_relaxed(p); }
            __syncwarp();
            g0 = __uint_as_float(v.x); g1 = __uint_as_float(v.z);
            g0 += __shfl_xor_sync(0xffffffffu, g0, 8);  g1 += __shfl_xor_sync(0xffffffffu, g1, 8);
            g0 += __shfl_xor_sync(0xffffffffu, g0, 16); g1 += __shfl_xor_sync(0xffffffffu, g1, 16);
            g0 = bf16r(silu_f(bf16r(g0))); g1 = bf16r(silu_f(bf16r(g1)));
        }
        if (tid == 0) {
            *reinterpret_cast<volatile uint32_t*>(smem + OFF_BAR + 208) = prog_v;
            prog_v = ld_relaxed32(&g_progress[0]);
        }
        const bool endgame = it >= NT - FK_ENDT;
        const char* k_next = kp + (size_t)(it + NST / 2) * STAGE_BYTES;
        const char* v_next = vp + (size_t)(it + NST / 2) * STAGE_BYTES;
        mbar_wait(bar_full + st * 8, ph);
        float c0[4] = {0.f, 0.f, 0.f, 0.f}, c1[4] = {0.f, 0.f, 0.f, 0.f};
        uint32_t relK = 0, pvK = 0;
        const uint32_t kb = k_base + st * STAGE_BYTES;
        {
#pragma unroll
            for (int j = 0; j < 8; j++) {
                uint32_t a[4];
                ldsm_x4(a, kb ^ (j << 4));
                mma_bf16((j & 1) ? c1 : c0, a, qf[j][0], qf[j][1]);
            }
            if (!endgame && seq < NSEQ && lane == 0) {
                relK = atom_inc_shared(cnt_rel + st * 4);
                pvK = lds32(prog_s);
            }
        }
        const float u0 = (g & 1) ? (c0[1] + c1[1]) : (c0[0] + c1[0]);
        const float u1 = (g & 1) ? (c0[3] + c1[3]) : (c0[2] + c1[2]);
        int key = __float_as_int(diag ? fmaxf(u0, u1) : -INFINITY);
        key ^= (key >> 31) & 0x7fffffff;
        key = __reduce_max_sync(0xffffffffu, key);
        const uint32_t r1 = pack_bf16(u0, u1);
        const uint32_t r2 = pack_bf16(bf_lo(r1) * RSQRT_DH, bf_hi(r1) * RSQRT_DH);
        const float s0 = diag ? bf_lo(r2) : -INFINITY, s1 = diag ? bf_hi(r2) : -INFINITY;
        key ^= (key >> 31) & 0x7fffffff;
        const float tmax = __int_as_float(key);
        if (tmax > m_raw) {
            m_raw = tmax;
            const float m_new = bf16r(bf16r(tmax) * RSQRT_DH);
            const float sc = ex2((m_run - m_new) * LOG2E);
#pragma unroll
            for (int i = 0; i < 4; i++) { acc0[i] *= sc; acc1[i] *= sc; }
            lacc[0] *= sc;
            m_run = m_new;
            mc = -m_new * LOG2E;
        }
        const uint32_t pk = pack_bf16(ex2(fmaf(s0, LOG2E, mc)), ex2(fmaf(s1, LOG2E, mc)));
        const uint32_t xx = __shfl_sync(0xffffffffu, pk, 9 * t), yy = __shfl_sync(0xffffffffu, pk, 9 * t + 4);
        const uint32_t pp0 = __byte_perm(xx, yy, 0x5410), pp1 = __byte_perm(xx, yy, 0x7632);
        if ((relK & (NCW - 1)) == NCW - 1) {
            pace(pvK, prog_base + (uint32_t)(it * N_ATT - (FK_LEAD)));
            issue_kv(k_next, st);
        }
        __syncwarp();
        const int stK = st;
        seq++;
        if (++st == NST) { st = 0; ph ^= 1; }
        mma_bf16(lacc, ones, pp0, pp1);
        if (it == NT - 1) {
            if (lane == 0) { ml_s[warp] = m_run; ml_s[8 + warp] = lacc[0]; }
            __syncthreads();
            const float4 ma = *reinterpret_cast<const float4*>(ml_s), mb = *reinterpret_cast<const float4*>(ml_s + 4);
            const float4 la = *reinterpret_cast<const float4*>(ml_s + 8), lb = *reinterpret_cast<const float4*>(ml_s + 12);
            const float M = fmaxf(fmaxf(fmaxf(ma.x, ma.y), fmaxf(ma.z, ma.w)), fmaxf(fmaxf(mb.x, mb.y), fmaxf(mb.z, mb.w)));
            const float L = (ex2((ma.x - M) * LOG2E) * la.x + ex2((ma.y - M) * LOG2E) * la.y) + (ex2((ma.z - M) * LOG2E) * la.z + ex2((ma.w - M) * LOG2E) * la.w)
                          + (ex2((mb.x - M) * LOG2E) * lb.x + ex2((mb.y - M) * LOG2E) * lb.y) + (ex2((mb.z - M) * LOG2E) * lb.z + ex2((mb.w - M) * LOG2E) * lb.w);
            fin_scale = __fdividef(ex2((m_run - M) * LOG2E), L);
        }
        mbar_wait(bar_full + st * 8, ph);
        const uint32_t vb = v_base + st * STAGE_BYTES;
        {
            uint32_t relV = 0, pvV = 0;
#pragma unroll
            for (int j = 0; j < 8; j++) {
                uint32_t a[4];
                ldsm_x4_t(a, vb ^ (j << 4));
                mma_bf16((j & 1) ? acc1 : acc0, a, pp0 & msk[j], pp1 & msk[j]);
            }
            if (seq - (endgame ? 1 : 0) < NSEQ && lane == 0) {
                relV = atom_inc_shared(cnt_rel + st * 4);
                pvV = lds32(prog_s);
            }
            if (tid == NTHREADS - 32) asm volatile("red.relaxed.gpu.global.add.u32 [%0], 1;" :: "l"(&g_progress[0]) : "memory");
            if ((relV & (NCW - 1)) == NCW - 1) {
                if (endgame) {
                    pace(pvV, prog_base + (uint32_t)((it + 1) * N_ATT - (FK_LEAD_END)));
                    issue_kv(k_next, stK);
                }
                if (seq < NSEQ) issue_kv(v_next, st);
            }
        }
        __syncwarp();
        seq++;
        if (++st == NST) { st = 0; ph ^= 1; }
    }

    {
        float* o = red_s + warp * 128;
        o[16 * t + g]          = (acc0[0] + acc1[0]) * fin_scale;
        o[16 * t + 8 + g]      = (acc0[1] + acc1[1]) * fin_scale;
        o[64 + 16 * t + g]     = (acc0[2] + acc1[2]) * fin_scale;
        o[64 + 16 * t + 8 + g] = (acc0[3] + acc1[3]) * fin_scale;
    }
    __syncthreads();
    if (tid < DH) {
        float v[8];
#pragma unroll
        for (int w = 0; w < 8; w++) v[w] = red_s[w * 128 + tid];
        const float o = ((v[0] + v[1]) + (v[2] + v[3])) + ((v[4] + v[5]) + (v[6] + v[7]));
        o_s[((tid >> 1) & 3) * 32 + (tid >> 4) * 4 + ((tid >> 3) & 1) * 2 + (tid & 1)] = __float2bfloat16_rn(o);
    }
    __syncthreads();
    {
        float d[4][4];
#pragma unroll
        for (int j = 0; j < 4; j++) { d[j][0] = d[j][1] = d[j][2] = d[j][3] = 0.f; }
        uint4 ov[4];
#pragma unroll
        for (int i = 0; i < 4; i++) ov[i] = *reinterpret_cast<const uint4*>(o_s + t * 32 + i * 8);
#pragma unroll
        for (int i = 0; i < 4; i++) {
#pragma unroll
            for (int j = 0; j < 4; j++) mma_bf16(d[j], wa[2 * i][j], ov[i].x, ov[i].y);
#pragma unroll
            for (int j = 0; j < 4; j++) mma_bf16(d[j], wa[2 * i + 1][j], ov[i].z, ov[i].w);
        }
        float r0 = d[0][0], r1 = d[0][2];
        if (t == 1) { r0 = d[1][0]; r1 = d[1][2]; }
        if (t == 2) { r0 = d[2][0]; r1 = d[2][2]; }
        if (t == 3) { r0 = d[3][0]; r1 = d[3][2]; }
        st_relaxed(a_out, make_uint4(__float_as_uint(r0), tag, __float_as_uint(r1), tag));
    }
    if (warp == 0) {
        const uint4* p = &g_attn_part[((b * 32 + h) * NH + q4 * 8) * 8 + cp];
        uint4 v[8];
#pragma unroll
        for (int i = 0; i < 8; i++) v[i] = ld_relaxed(p + i * 8);
        for (int spin = 0; spin < (1 << 20); spin++) {
            bool ok = true;
#pragma unroll
            for (int i = 0; i < 8; i++) {
                if (!ll_valid(v[i], tag)) { v[i] = ld_relaxed(p + i * 8); ok = false; }
            }
            if (ok) break;
        }
        __syncwarp();
        float s0 = ((__uint_as_float(v[0].x) + __uint_as_float(v[1].x)) + (__uint_as_float(v[2].x) + __uint_as_float(v[3].x)))
                 + ((__uint_as_float(v[4].x) + __uint_as_float(v[5].x)) + (__uint_as_float(v[6].x) + __uint_as_float(v[7].x)));
        float s1 = ((__uint_as_float(v[0].z) + __uint_as_float(v[1].z)) + (__uint_as_float(v[2].z) + __uint_as_float(v[3].z)))
                 + ((__uint_as_float(v[4].z) + __uint_as_float(v[5].z)) + (__uint_as_float(v[6].z) + __uint_as_float(v[7].z)));
        s0 += __shfl_xor_sync(0xffffffffu, s0, 8);  s1 += __shfl_xor_sync(0xffffffffu, s1, 8);
        s0 += __shfl_xor_sync(0xffffffffu, s0, 16); s1 += __shfl_xor_sync(0xffffffffu, s1, 16);
        if (lane < 8) {
            out[b * DM + h * 16 + cp]     = __float2bfloat16_rn(x0 + bf16r(bf16r(s0) * g0));
            out[b * DM + h * 16 + 8 + cp] = __float2bfloat16_rn(x1 + bf16r(bf16r(s1) * g1));
        }
        if (lane == 0) { g_epoch[cta] = tag + 1; }
    }
}

}

extern "C" void kernel_launch(void* const* d_in, const int* in_sizes, int n_in, void* d_out, int out_size) {
    (void)in_sizes; (void)n_in; (void)out_size;
    const __nv_bfloat16* x  = (const __nv_bfloat16*)d_in[0];
    const __nv_bfloat16* Kc = (const __nv_bfloat16*)d_in[1];
    const __nv_bfloat16* Vc = (const __nv_bfloat16*)d_in[2];
    const __nv_bfloat16* wq = (const __nv_bfloat16*)d_in[3];
    const __nv_bfloat16* wo = (const __nv_bfloat16*)d_in[4];
    const __nv_bfloat16* w1 = (const __nv_bfloat16*)d_in[6];
    const __nv_bfloat16* w2 = (const __nv_bfloat16*)d_in[7];

    static bool attr_set = false;
    if (!attr_set) {
        cudaFuncSetAttribute(fk::fused_decode_kernel, cudaFuncAttributeMaxDynamicSharedMemorySize, fk::SMEM_BYTES);
        attr_set = true;
    }
    fk::fused_decode_kernel<<<fk::N_CTA, fk::NTHREADS, fk::SMEM_BYTES>>>(x, Kc, Vc, wq, wo, w1, w2, (__nv_bfloat16*)d_out);
}
```

```cpp
#include <cuda_runtime.h>
#include <cuda_bf16.h>
#include <stdint.h>

namespace fk {

#define FK_NST 4
#define FK_FIRST 2
#define FK_PRE 1
#define FK_WTILE 4
#define FK_WSTEP 10
#define FK_LEAD 0
#define FK_ENDT 16
#define FK_LEAD_END 40

constexpr int NB = 4, NH = 32, SK = 8192, DH = 128, DM = 512, FF = 1376;
constexpr int TK = 128;
constexpr int NT = SK / TK;
constexpr int STAGE_BYTES = TK * DH * 2;
constexpr int NST = FK_NST;
constexpr int NCW = 8;
constexpr int NTHREADS = NCW * 32;
constexpr int N_ATT = NB * NH;
constexpr int N_FFN = 4;
constexpr int FS = FF / N_FFN;
constexpr int N_CTA = N_ATT + N_FFN;
constexpr int NSEQ = 2 * NT;
static_assert(NST % 2 == 0, "K tiles live in the even stages, V tiles in the odd ones");

constexpr int OFF_W   = NST * STAGE_BYTES;
constexpr int OFF_XN  = OFF_W;
constexpr int OFF_X   = OFF_W + 8192;
constexpr int OFF_RED = OFF_W + 12288;
constexpr int OFF_BAR = OFF_W + STAGE_BYTES;
constexpr int OFF_Q   = OFF_BAR + 256;
constexpr int OFF_ML  = OFF_Q + 256;
constexpr int OFF_O   = OFF_ML + 64;
constexpr int SMEM_ATT = OFF_O + 256;
constexpr int FFN_CHUNK = 64 * FS * 2;
constexpr int NBF = (NST >= 6) ? 4 : 2;
constexpr int FFN_XN = NBF * FFN_CHUNK, FFN_H = FFN_XN + 8192, FFN_RED = FFN_H + 5504, FFN_BAR = FFN_RED + 32768;
constexpr int SMEM_FFN = FFN_BAR + 64;
static_assert(FFN_CHUNK == 43 * DM * 2, "chunk geometry");
constexpr int SMEM_BYTES = SMEM_ATT > SMEM_FFN ? SMEM_ATT : SMEM_FFN;

__device__ __align__(256) uint4 g_q_part[NH * NB * 32];
__device__ __align__(256) uint4 g_attn_part[NB * 32 * NH * 8];
__device__ __align__(256) uint4 g_ffn_part[NB * 32 * N_FFN * 8];
__device__ __align__(256) uint32_t g_progress[64];
#define FK_ONE4 1u, 1u, 1u, 1u
#define FK_ONE16 FK_ONE4, FK_ONE4, FK_ONE4, FK_ONE4
#define FK_ONE64 FK_ONE16, FK_ONE16, FK_ONE16, FK_ONE16
__device__ __align__(256) uint32_t g_epoch[N_CTA] = {FK_ONE64, FK_ONE64, FK_ONE4};

__device__ __forceinline__ uint32_t smem_u32(const void* p) { return (uint32_t)__cvta_generic_to_shared(p); }

__device__ __forceinline__ void mbar_init(uint32_t bar, uint32_t cnt) {
    asm volatile("mbarrier.init.shared::cta.b64 [%0], %1;" :: "r"(bar), "r"(cnt) : "memory");
}
__device__ __forceinline__ void mbar_expect_tx(uint32_t bar, uint32_t bytes) {
    asm volatile("mbarrier.arrive.expect_tx.shared::cta.b64 _, [%0], %1;" :: "r"(bar), "r"(bytes) : "memory");
}
__device__ __forceinline__ uint32_t atom_inc_shared(uint32_t addr) {
    uint32_t old;
    asm volatile("atom.relaxed.cta.shared::cta.add.u32 %0, [%1], 1;" : "=r"(old) : "r"(addr) : "memory");
    return old;
}
__device__ __forceinline__ void mbar_wait(uint32_t bar, uint32_t parity) {
    asm volatile(
        "{\n"
        ".reg .pred p;\n"
        "FK_WAIT:\n"
        "mbarrier.try_wait.parity.shared::cta.b64 p, [%0], %1;\n"
        "@p bra FK_DONE;\n"
        "bra FK_WAIT;\n"
        "FK_DONE:\n"
        "}\n" :: "r"(bar), "r"(parity) : "memory");
}
__device__ __forceinline__ void bulk_load(uint32_t dst, const void* src, uint32_t bytes, uint32_t bar, uint64_t pol) {
    asm volatile("cp.async.bulk.shared::cluster.global.mbarrier::complete_tx::bytes.L2::cache_hint [%0], [%1], %2, [%3], %4;"
                 :: "r"(dst), "l"(src), "r"(bytes), "r"(bar), "l"(pol) : "memory");
}
__device__ __forceinline__ uint4 ldg_nc(const void* p) {
    uint4 v;
    asm volatile("ld.global.nc.L1::no_allocate.v4.u32 {%0,%1,%2,%3}, [%4];"
                 : "=r"(v.x), "=r"(v.y), "=r"(v.z), "=r"(v.w) : "l"(p));
    return v;
}
__device__ __forceinline__ void bulk_load_plain(uint32_t dst, const void* src, uint32_t bytes, uint32_t bar) {
    asm volatile("cp.async.bulk.shared::cluster.global.mbarrier::complete_tx::bytes [%0], [%1], %2, [%3];"
                 :: "r"(dst), "l"(src), "r"(bytes), "r"(bar) : "memory");
}
__device__ __forceinline__ uint32_t ldg_nc32(const void* p) {
    uint32_t v;
    asm volatile("ld.global.nc.L1::no_allocate.u32 %0, [%1];" : "=r"(v) : "l"(p));
    return v;
}
__device__ __forceinline__ uint32_t lds32(uint32_t addr) {
    uint32_t v;
    asm volatile("ld.volatile.shared.u32 %0, [%1];" : "=r"(v) : "r"(addr) : "memory");
    return v;
}
__device__ __forceinline__ uint32_t pin(uint32_t v) {
    uint32_t r;
    asm volatile("mov.b32 %0, %1;" : "=r"(r) : "r"(v));
    return r;
}
__device__ __forceinline__ uint32_t ld_relaxed32(const uint32_t* p) {
    uint32_t v;
    asm volatile("ld.relaxed.gpu.global.u32 %0, [%1];" : "=r"(v) : "l"(p) : "memory");
    return v;
}
__device__ __forceinline__ bool mbar_test(uint32_t bar, uint32_t parity) {
    uint32_t ok;
    asm volatile("{\n.reg .pred p;\nmbarrier.test_wait.parity.shared::cta.b64 p, [%1], %2;\nselp.u32 %0, 1, 0, p;\n}\n"
                 : "=r"(ok) : "r"(bar), "r"(parity) : "memory");
    return ok != 0;
}
__device__ __forceinline__ uint4 ld_relaxed(const uint4* p) {
    uint4 v;
    asm volatile("ld.relaxed.gpu.global.v4.u32 {%0,%1,%2,%3}, [%4];"
                 : "=r"(v.x), "=r"(v.y), "=r"(v.z), "=r"(v.w) : "l"(p) : "memory");
    return v;
}
__device__ __forceinline__ void st_relaxed(uint4* p, uint4 v) {
    asm volatile("st.relaxed.gpu.global.v4.u32 [%0], {%1,%2,%3,%4};"
                 :: "l"(p), "r"(v.x), "r"(v.y), "r"(v.z), "r"(v.w) : "memory");
}
__device__ __forceinline__ void ldsm_x4(uint32_t (&r)[4], uint32_t addr) {
    asm volatile("ldmatrix.sync.aligned.m8n8.x4.shared.b16 {%0,%1,%2,%3}, [%4];"
                 : "=r"(r[0]), "=r"(r[1]), "=r"(r[2]), "=r"(r[3]) : "r"(addr) : "memory");
}
__device__ __forceinline__ void ldsm_x4_t(uint32_t (&r)[4], uint32_t addr) {
    asm volatile("ldmatrix.sync.aligned.m8n8.x4.trans.shared.b16 {%0,%1,%2,%3}, [%4];"
                 : "=r"(r[0]), "=r"(r[1]), "=r"(r[2]), "=r"(r[3]) : "r"(addr) : "memory");
}
__device__ __forceinline__ void mma_bf16(float (&c)[4], const uint32_t (&a)[4], uint32_t b0, uint32_t b1) {
    asm volatile("mma.sync.aligned.m16n8k16.row.col.f32.bf16.bf16.f32 {%0,%1,%2,%3}, {%4,%5,%6,%7}, {%8,%9}, {%0,%1,%2,%3};"
                 : "+f"(c[0]), "+f"(c[1]), "+f"(c[2]), "+f"(c[3])
                 : "r"(a[0]), "r"(a[1]), "r"(a[2]), "r"(a[3]), "r"(b0), "r"(b1));
}
__device__ __forceinline__ float ex2(float x) {
    float r;
    asm("ex2.approx.ftz.f32 %0, %1;" : "=f"(r) : "f"(x));
    return r;
}
__device__ __forceinline__ uint32_t pack_bf16(float lo, float hi) {
    uint32_t r;
    asm("cvt.rn.bf16x2.f32 %0, %1, %2;" : "=r"(r) : "f"(hi), "f"(lo));
    return r;
}
__device__ __forceinline__ float bf_lo(uint32_t w) { return __uint_as_float(w << 16); }
__device__ __forceinline__ float bf_hi(uint32_t w) { return __uint_as_float(w & 0xffff0000u); }
__device__ __forceinline__ float bf16r(float x) { return __bfloat162float(__float2bfloat16_rn(x)); }
__device__ __forceinline__ float silu_f(float x) { return x / (1.0f + __expf(-x)); }

__device__ __forceinline__ void warp_layernorm(const uint4 a, const uint4 b, float (&xn)[16]) {
    float v[16];
    v[0] = bf_lo(a.x); v[1] = bf_hi(a.x); v[2] = bf_lo(a.y); v[3] = bf_hi(a.y);
    v[4] = bf_lo(a.z); v[5] = bf_hi(a.z); v[6] = bf_lo(a.w); v[7] = bf_hi(a.w);
    v[8] = bf_lo(b.x); v[9] = bf_hi(b.x); v[10] = bf_lo(b.y); v[11] = bf_hi(b.y);
    v[12] = bf_lo(b.z); v[13] = bf_hi(b.z); v[14] = bf_lo(b.w); v[15] = bf_hi(b.w);
    float s = 0.f;
#pragma unroll
    for (int i = 0; i < 16; i++) s += v[i];
#pragma unroll
    for (int o = 16; o; o >>= 1) s += __shfl_xor_sync(0xffffffffu, s, o);
    const float mean = s * (1.0f / DM);
    float ss = 0.f;
#pragma unroll
    for (int i = 0; i < 16; i++) { const float d = v[i] - mean; ss = fmaf(d, d, ss); }
#pragma unroll
    for (int o = 16; o; o >>= 1) ss += __shfl_xor_sync(0xffffffffu, ss, o);
    const float m_bf = bf16r(mean);
    const float den = bf16r(sqrtf(bf16r(bf16r(ss * (1.0f / DM)) + 1e-5f)));
#pragma unroll
    for (int i = 0; i < 16; i++) xn[i] = bf16r(__fdiv_rn(bf16r(v[i] - m_bf), den));
}

__device__ __forceinline__ bool ll_valid(const uint4& v, uint32_t tag) { return v.y == tag && v.w == tag; }

__device__ __forceinline__ void ffn_cta(uint8_t* smem, int f, uint32_t tag,
                                        const __nv_bfloat16* __restrict__ x,
                                        const __nv_bfloat16* __restrict__ w1,
                                        const __nv_bfloat16* __restrict__ w2) {
    const int tid = threadIdx.x, warp = tid >> 5, lane = tid & 31;
    const uint32_t sbase = smem_u32(smem), bar = sbase + FFN_BAR;
    float* xnT = reinterpret_cast<float*>(smem + FFN_XN);
    float* hT  = reinterpret_cast<float*>(smem + FFN_H);
    float* red = reinterpret_cast<float*>(smem + FFN_RED);
    if (tid == 0) {
#pragma unroll
        for (int s = 0; s < NBF; s++) mbar_init(bar + s * 8, 1);
    }
    __syncthreads();
    auto issue = [&](int c) {
        const int s = c % NBF;
        if (tid == 0) mbar_expect_tx(bar + s * 8, FFN_CHUNK);
        if (c < 8) {
            __syncthreads();
            if (tid < 64) bulk_load_plain(sbase + s * FFN_CHUNK + tid * (FS * 2), w1 + (size_t)(c * 64 + tid) * FF + f * FS, FS * 2, bar + s * 8);
        } else if (tid == 0) {
            bulk_load_plain(sbase + s * FFN_CHUNK, w2 + (size_t)(f * FS + (c - 8) * 43) * DM, FFN_CHUNK, bar + s * 8);
        }
    };
    for (int c = 0; c < NBF; c++) issue(c);
    if (warp < NB) {
        float xn[16];
        const uint4 xa = ldg_nc(x + warp * DM + lane * 16), xb = ldg_nc(x + warp * DM + lane * 16 + 8);
        warp_layernorm(xa, xb, xn);
#pragma unroll
        for (int i = 0; i < 16; i++) xnT[(lane * 16 + i) * 4 + warp] = xn[i];
    }
    __syncthreads();
    float acc[4][8];
#pragma unroll
    for (int b = 0; b < 4; b++)
#pragma unroll
        for (int c = 0; c < 8; c++) acc[b][c] = 0.f;
#pragma unroll 1
    for (int c = 0; c < 16; c++) {
        const int s = c % NBF;
        mbar_wait(bar + s * 8, (c / NBF) & 1);
        const bool st1 = c < 8;
        const int cg = st1 ? tid % 43 : (tid & 63), r0 = st1 ? tid / 43 : (tid >> 6);
        const int rstep = st1 ? 5 : 4, nrows = st1 ? 64 : 43, rbytes = st1 ? FS * 2 : DM * 2;
        const float* vec = st1 ? xnT + c * 64 * 4 : hT + (c - 8) * 43 * 4;
        const uint8_t* wb = smem + s * FFN_CHUNK + cg * 16;
        if (!st1 || tid < 43 * 5) {
#pragma unroll 2
            for (int k = r0; k < nrows; k += rstep) {
                const uint4 w = *reinterpret_cast<const uint4*>(wb + k * rbytes);
                const float4 xv = *reinterpret_cast<const float4*>(vec + k * 4);
                const float wf[8] = {bf_lo(w.x), bf_hi(w.x), bf_lo(w.y), bf_hi(w.y), bf_lo(w.z), bf_hi(w.z), bf_lo(w.w), bf_hi(w.w)};
#pragma unroll
                for (int j = 0; j < 8; j++) {
                    acc[0][j] = fmaf(xv.x, wf[j], acc[0][j]);
                    acc[1][j] = fmaf(xv.y, wf[j], acc[1][j]);
                    acc[2][j] = fmaf(xv.z, wf[j], acc[2][j]);
                    acc[3][j] = fmaf(xv.w, wf[j], acc[3][j]);
                }
            }
        }
        __syncthreads();
        if (c + NBF < 16) issue(c + NBF);
        if (c == 7) {
            if (tid < 43 * 5) {
#pragma unroll
                for (int b = 0; b < 4; b++)
#pragma unroll
                    for (int j = 0; j < 8; j++) red[(r0 * 4 + b) * FS + cg * 8 + j] = acc[b][j];
            }
#pragma unroll
            for (int b = 0; b < 4; b++)
#pragma unroll
                for (int j = 0; j < 8; j++) acc[b][j] = 0.f;
            __syncthreads();
            for (int i = tid; i < 4 * FS; i += NTHREADS) {
                const int b = i / FS, cc = i % FS;
                float sum = 0.f;
#pragma unroll
                for (int ks = 0; ks < 5; ks++) sum += red[(ks * 4 + b) * FS + cc];
                hT[cc * 4 + b] = bf16r(silu_f(bf16r(sum)));
            }
            __syncthreads();
        }
    }
    {
        const int cg = tid & 63, fs = tid >> 6;
#pragma unroll
        for (int b = 0; b < 4; b++)
#pragma unroll
            for (int j = 0; j < 8; j++) red[(fs * 4 + b) * DM + cg * 8 + j] = acc[b][j];
    }
    __syncthreads();
    for (int i = tid; i < NB * 256; i += NTHREADS) {
        const int b = i >> 8, j = (i >> 3) & 31, p = i & 7;
        float s0 = 0.f, s1 = 0.f;
#pragma unroll
        for (int fs = 0; fs < 4; fs++) { s0 += red[(fs * 4 + b) * DM + 16 * j + p]; s1 += red[(fs * 4 + b) * DM + 16 * j + 8 + p]; }
        st_relaxed(&g_ffn_part[((b * 32 + j) * N_FFN + f) * 8 + p],
                   make_uint4(__float_as_uint(s0), tag, __float_as_uint(s1), tag));
    }
}

__global__ void __launch_bounds__(NTHREADS, 1)
fused_decode_kernel(const __nv_bfloat16* __restrict__ x, const __nv_bfloat16* __restrict__ Kc,
                    const __nv_bfloat16* __restrict__ Vc, const __nv_bfloat16* __restrict__ wq,
                    const __nv_bfloat16* __restrict__ wo, const __nv_bfloat16* __restrict__ w1,
                    const __nv_bfloat16* __restrict__ w2, __nv_bfloat16* __restrict__ out) {
    extern __shared__ __align__(1024) uint8_t smem[];
    const int cta = blockIdx.x;
    const int tid = threadIdx.x, warp = tid >> 5, lane = tid & 31;
    if (cta >= N_ATT) {
        const uint32_t tag = ld_relaxed32(&g_epoch[cta]);
        ffn_cta(smem, cta - N_ATT, tag, x, w1, w2);
        if (tid == 0) { g_epoch[cta] = tag + 1; }
        return;
    }

    const int b = cta & 3, h = cta >> 2;
    const int bh = b * NH + h;
    const uint32_t sbase = pin(smem_u32(smem));
    const uint32_t bar_full = sbase + OFF_BAR;
    const uint32_t cnt_rel = bar_full + NST * 8;
    const char* kp = reinterpret_cast<const char*>(Kc) + (size_t)bh * SK * DH * 2;
    const char* vp = reinterpret_cast<const char*>(Vc) + (size_t)bh * SK * DH * 2;
    const char* wop = reinterpret_cast<const char*>(wo) + (size_t)h * DH * DM * 2;
    uint64_t pol;
    asm volatile("createpolicy.fractional.L2::evict_first.b64 %0, 1.0;" : "=l"(pol));
    auto issue_kv = [&](const char* src, int s) {
        const uint32_t bar = bar_full + s * 8;
        mbar_expect_tx(bar, STAGE_BYTES);
        bulk_load(sbase + s * STAGE_BYTES, src, STAGE_BYTES, bar, pol);
    };
    auto issue_first = [&](int n) { issue_kv(((n & 1) ? vp : kp) + (size_t)(n >> 1) * STAGE_BYTES, n); };
    const uint32_t bar_w = bar_full + 216, cnt_w = bar_full + 224;
    auto issue_w = [&](int q) {
        mbar_expect_tx(bar_w, STAGE_BYTES);
        bulk_load_plain(sbase + OFF_W, wop + (size_t)q * STAGE_BYTES, STAGE_BYTES, bar_w);
    };

    const int g = lane >> 2, t = lane & 3;
    float* xn_s  = reinterpret_cast<float*>(smem + OFF_XN);
    float* red_s = reinterpret_cast<float*>(smem + OFF_RED);
    __nv_bfloat16* q_s = reinterpret_cast<__nv_bfloat16*>(smem + OFF_Q);
    float* ml_s = reinterpret_cast<float*>(smem + OFF_ML);
    __nv_bfloat16* o_s = reinterpret_cast<__nv_bfloat16*>(smem + OFF_O);

    uint4* const q_out = &g_q_part[(h * NB + (lane >> 3)) * 32 + b * 8 + (lane & 7)];
    uint4* const a_out = &g_attn_part[((b * 32 + warp * 4 + t) * NH + h) * 8 + g];

    volatile uint32_t* q_flag = reinterpret_cast<volatile uint32_t*>(smem + OFF_BAR + 192);
    const uint32_t bar_x = bar_full + 200;
    if (tid == 0) {
        mbar_init(bar_full, 1);
        issue_first(0);
        mbar_init(bar_x, 1);
        mbar_expect_tx(bar_x, NB * DM * 2);
        bulk_load_plain(sbase + OFF_X, x, NB * DM * 2, bar_x);
#pragma unroll
        for (int s = 1; s < NST; s++) mbar_init(bar_full + s * 8, 1);
        mbar_init(bar_w, 1);
#pragma unroll
        for (int s = 0; s < NST; s++) *reinterpret_cast<volatile uint32_t*>(smem + OFF_BAR + NST * 8 + s * 4) = 0;
        *reinterpret_cast<volatile uint32_t*>(smem + OFF_BAR + 224) = 0;
        *q_flag = 0;
#pragma unroll 1
        for (int s = 1; s < FK_PRE; s++) issue_first(s);
    }
    uint32_t qf[8][2];
    uint32_t tag;
    {
        uint32_t w[32];
        const __nv_bfloat16* wp = wq + (size_t)(warp * 64 + (lane >> 4) * 32) * (NH * DH) + h * DH + b * 32 + (lane & 15) * 2;
#pragma unroll
        for (int i = 0; i < 32; i++) w[i] = ldg_nc32(wp + (size_t)i * (NH * DH));
        tag = ld_relaxed32(&g_epoch[cta]);
        if (tid == 0) {
#pragma unroll 1
            for (int s = FK_PRE; s < FK_FIRST; s++) issue_first(s);
            asm volatile("prefetch.global.L2 [%0];" :: "l"(wop));
        }
        if (warp == 0) st_relaxed(q_out, make_uint4(0, 0, 0, 0));
        st_relaxed(a_out, make_uint4(0, 0, 0, 0));
        __syncthreads();
        if (warp < 4) {
            float xn[16];
            mbar_wait(bar_x, 0);
            const uint4 xa = *reinterpret_cast<const uint4*>(smem + OFF_X + warp * DM * 2 + lane * 32);
            const uint4 xb = *reinterpret_cast<const uint4*>(smem + OFF_X + warp * DM * 2 + lane * 32 + 16);
            warp_layernorm(xa, xb, xn);
#pragma unroll
            for (int i = 0; i < 16; i += 4)
                *reinterpret_cast<float4*>(xn_s + warp * DM + lane * 16 + i) = make_float4(xn[i], xn[i + 1], xn[i + 2], xn[i + 3]);
        }
        __syncthreads();
        float acc[4][2];
#pragma unroll
        for (int bb = 0; bb < 4; bb++) acc[bb][0] = acc[bb][1] = 0.f;
        const float* xp = xn_s + warp * 64 + (lane >> 4) * 32;
#pragma unroll
        for (int i4 = 0; i4 < 8; i4++) {
#pragma unroll
            for (int bb = 0; bb < 4; bb++) {
                const float4 xv = *reinterpret_cast<const float4*>(xp + bb * DM + i4 * 4);
                const float xs[4] = {xv.x, xv.y, xv.z, xv.w};
#pragma unroll
                for (int u = 0; u < 4; u++) {
                    acc[bb][0] = fmaf(xs[u], bf_lo(w[i4 * 4 + u]), acc[bb][0]);
                    acc[bb][1] = fmaf(xs[u], bf_hi(w[i4 * 4 + u]), acc[bb][1]);
                }
            }
        }
        const bool up = lane >= 16;
        float k0 = up ? acc[2][0] : acc[0][0], k1 = up ? acc[2][1] : acc[0][1];
        float k2 = up ? acc[3][0] : acc[1][0], k3 = up ? acc[3][1] : acc[1][1];
        k0 += __shfl_xor_sync(0xffffffffu, up ? acc[0][0] : acc[2][0], 16);
        k1 += __shfl_xor_sync(0xffffffffu, up ? acc[0][1] : acc[2][1], 16);
        k2 += __shfl_xor_sync(0xffffffffu, up ? acc[1][0] : acc[3][0], 16);
        k3 += __shfl_xor_sync(0xffffffffu, up ? acc[1][1] : acc[3][1], 16);
        float* rp = red_s + warp * 128 + (up ? 64 : 0) + (lane & 15) * 2;
        *reinterpret_cast<float2*>(rp)      = make_float2(k0, k1);
        *reinterpret_cast<float2*>(rp + 32) = make_float2(k2, k3);
        __syncthreads();
        if (warp == 0) {
            float4 s = make_float4(0.f, 0.f, 0.f, 0.f);
#pragma unroll
            for (int w8 = 0; w8 < NCW; w8++) {
                const float4 v = *reinterpret_cast<const float4*>(red_s + w8 * 128 + lane * 4);
                s.x += v.x; s.y += v.y; s.z += v.z; s.w += v.w;
            }
            st_relaxed(q_out, make_uint4(pack_bf16(s.x, s.y), tag, pack_bf16(s.z, s.w), tag));
            const uint4* p = &g_q_part[(h * NB + b) * 32 + lane];
            uint4 v = ld_relaxed(p);
            for (int spin = 0; !ll_valid(v, tag) && spin < (1 << 20); spin++) v = ld_relaxed(p);
            *reinterpret_cast<uint2*>(q_s + lane * 4) = make_uint2(v.x, v.z);
            if (lane == 0) *q_flag = 1;
        }
        if (tid == NTHREADS - 32) {
            int next = FK_FIRST, watch = 0;
            while (next < NST) {
                if (mbar_test(bar_full + watch * 8, 0)) { issue_first(next); next++; watch++; }
                else if (*q_flag) break;
            }
#pragma unroll 1
            for (; next < NST; next++) issue_first(next);
        }
        __syncthreads();
#pragma unroll
        for (int j = 0; j < 8; j++) {
            const int c = (j ^ g) & 7;
            qf[j][0] = *reinterpret_cast<const uint32_t*>(q_s + c * 8 + 2 * t);
            qf[j][1] = *reinterpret_cast<const uint32_t*>(q_s + 64 + c * 8 + 2 * t);
        }
    }

    constexpr float RSQRT_DH = 0.08838834764831845f, LOG2E = 1.4426950408889634f;
    const int li = lane & 7, lm = lane >> 3;
    const uint32_t k_base = pin(sbase + (uint32_t)((warp * 16 + li + 8 * (lm & 1)) * 256 + (lm >> 1) * 128 + li * 16));
    const uint32_t v_base = pin(sbase + (uint32_t)((warp * 16 + li + 8 * (lm >> 1)) * 256 + (lm & 1) * 128 + li * 16));
    const bool diag = (t == (g >> 1));
    uint32_t msk[8];
#pragma unroll
    for (int j = 0; j < 8; j++) msk[j] = pin((j == (g ^ (2 * t)) ? 0x0000ffffu : 0u) | (j == (g ^ (2 * t) ^ 1) ? 0xffff0000u : 0u));
    const uint32_t ones[4] = {0x3f803f80u, 0x3f803f80u, 0x3f803f80u, 0x3f803f80u};

    float acc0[4] = {0.f, 0.f, 0.f, 0.f}, acc1[4] = {0.f, 0.f, 0.f, 0.f}, lacc[4] = {0.f, 0.f, 0.f, 0.f};
    float m_raw = -INFINITY;
    float m_run = -INFINITY, mc = 0.f;
    float fin_scale = 0.f;
    int st = 0; uint32_t ph = 0;
    int seq = NST;
    uint32_t wa[8][4][4];
    float g0 = 0.f, g1 = 0.f;
    uint4 gv = make_uint4(0, 0, 0, 0);
    const int cp = lane & 7, q4 = lane >> 3;
    const float x0 = __bfloat162float(reinterpret_cast<const __nv_bfloat16*>(smem + OFF_X)[b * DM + h * 16 + cp]);
    const float x1 = __bfloat162float(reinterpret_cast<const __nv_bfloat16*>(smem + OFF_X)[b * DM + h * 16 + 8 + cp]);
    const uint32_t prog_base = (tag - 1) * (uint32_t)(N_ATT * NT);
    const uint32_t prog_s = bar_full + 208;
    uint32_t prog_v = prog_base;
    if (tid == 0) *reinterpret_cast<volatile uint32_t*>(smem + OFF_BAR + 208) = prog_base;
    __syncthreads();
    auto pace = [&](uint32_t pv, uint32_t lim) {
        for (int spin = 0; (int)(pv - lim) < 0 && spin < 4096; spin++) pv = ld_relaxed32(&g_progress[0]);
    };

#pragma unroll 1
    for (int it = 0; it < NT; it++) {
#pragma unroll
        for (int q = 0; q <= 4; q++) {
            if (it == FK_WTILE + q * FK_WSTEP) {
                if (q == 0) {
                    if (tid == 0) {
                        asm volatile("fence.proxy.async.shared::cta;" ::: "memory");
                        issue_w(0);
                    }
                } else {
                    mbar_wait(bar_w, (q - 1) & 1);
                    const uint32_t wb = sbase + OFF_W + (li + 8 * (lane >> 4)) * 1024 + warp * 128 + (lm & 1) * 16;
#pragma unroll
                    for (int j = 0; j < 4; j++) {
                        ldsm_x4_t(wa[2 * q - 2][j], wb + j * 32);
                        ldsm_x4_t(wa[2 * q - 1][j], wb + 16384 + j * 32);
                    }
                    if (q < 4 && lane == 0) {
                        const uint32_t rel = atom_inc_shared(cnt_w);
                        if ((rel & (NCW - 1)) == NCW - 1) issue_w(q);
                    }
                }
                __syncwarp();
            }
        }
        if (it == NT - 12 && warp == 0) {
            gv = ld_relaxed(&g_ffn_part[((b * 32 + h) * N_FFN + q4) * 8 + cp]);
        }
        if (it == NT - 2 && warp == 0) {
            const uint4* p = &g_ffn_part[((b * 32 + h) * N_FFN + q4) * 8 + cp];
            uint4 v = gv;
            for (int spin = 0; !ll_valid(v, tag) && spin < (1 << 20); spin++) { __nanosleep(64); v = ld_relaxed(p); }
            __syncwarp();
            g0 = __uint_as_float(v.x); g1 = __uint_as_float(v.z);
            g0 += __shfl_xor_sync(0xffffffffu, g0, 8);  g1 += __shfl_xor_sync(0xffffffffu, g1, 8);
            g0 += __shfl_xor_sync(0xffffffffu, g0, 16); g1 += __shfl_xor_sync(0xffffffffu, g1, 16);
            g0 = bf16r(silu_f(bf16r(g0))); g1 = bf16r(silu_f(bf16r(g1)));
        }
        if (tid == 0) {
            *reinterpret_cast<volatile uint32_t*>(smem + OFF_BAR + 208) = prog_v;
            prog_v = ld_relaxed32(&g_progress[0]);
        }
        const bool endgame = it >= NT - FK_ENDT;
        const char* k_next = kp + (size_t)(it + NST / 2) * STAGE_BYTES;
        const char* v_next = vp + (size_t)(it + NST / 2) * STAGE_BYTES;
        mbar_wait(bar_full + st * 8, ph);
        float c0[4] = {0.f, 0.f, 0.f, 0.f}, c1[4] = {0.f, 0.f, 0.f, 0.f};
        uint32_t relK = 0, pvK = 0;
        const uint32_t kb = k_base + st * STAGE_BYTES;
        {
#pragma unroll
            for (int j = 0; j < 8; j++) {
                uint32_t a[4];
                ldsm_x4(a, kb ^ (j << 4));
                mma_bf16((j & 1) ? c1 : c0, a, qf[j][0], qf[j][1]);
            }
            if (!endgame && seq < NSEQ && lane == 0) {
                relK = atom_inc_shared(cnt_rel + st * 4);
                pvK = lds32(prog_s);
            }
        }
        const float u0 = (g & 1) ? (c0[1] + c1[1]) : (c0[0] + c1[0]);
        const float u1 = (g & 1) ? (c0[3] + c1[3]) : (c0[2] + c1[2]);
        int key = __float_as_int(diag ? fmaxf(u0, u1) : -INFINITY);
        key ^= (key >> 31) & 0x7fffffff;
        key = __reduce_max_sync(0xffffffffu, key);
        const uint32_t r1 = pack_bf16(u0, u1);
        const uint32_t r2 = pack_bf16(bf_lo(r1) * RSQRT_DH, bf_hi(r1) * RSQRT_DH);
        const float s0 = diag ? bf_lo(r2) : -INFINITY, s1 = diag ? bf_hi(r2) : -INFINITY;
        key ^= (key >> 31) & 0x7fffffff;
        const float tmax = __int_as_float(key);
        if (tmax > m_raw) {
            m_raw = tmax;
            const float m_new = bf16r(bf16r(tmax) * RSQRT_DH);
            const float sc = ex2((m_run - m_new) * LOG2E);
#pragma unroll
            for (int i = 0; i < 4; i++) { acc0[i] *= sc; acc1[i] *= sc; }
            lacc[0] *= sc;
            m_run = m_new;
            mc = -m_new * LOG2E;
        }
        const uint32_t pk = pack_bf16(ex2(fmaf(s0, LOG2E, mc)), ex2(fmaf(s1, LOG2E, mc)));
        const uint32_t xx = __shfl_sync(0xffffffffu, pk, 9 * t), yy = __shfl_sync(0xffffffffu, pk, 9 * t + 4);
        const uint32_t pp0 = __byte_perm(xx, yy, 0x5410), pp1 = __byte_perm(xx, yy, 0x7632);
        if ((relK & (NCW - 1)) == NCW - 1) {
            pace(pvK, prog_base + (uint32_t)(it * N_ATT - (FK_LEAD)));
            issue_kv(k_next, st);
        }
        __syncwarp();
        const int stK = st;
        seq++;
        if (++st == NST) { st = 0; ph ^= 1; }
        mma_bf16(lacc, ones, pp0, pp1);
        if (it == NT - 1) {
            if (lane == 0) { ml_s[warp] = m_run; ml_s[8 + warp] = lacc[0]; }
            __syncthreads();
            const float4 ma = *reinterpret_cast<const float4*>(ml_s), mb = *reinterpret_cast<const float4*>(ml_s + 4);
            const float4 la = *reinterpret_cast<const float4*>(ml_s + 8), lb = *reinterpret_cast<const float4*>(ml_s + 12);
            const float M = fmaxf(fmaxf(fmaxf(ma.x, ma.y), fmaxf(ma.z, ma.w)), fmaxf(fmaxf(mb.x, mb.y), fmaxf(mb.z, mb.w)));
            const float L = (ex2((ma.x - M) * LOG2E) * la.x + ex2((ma.y - M) * LOG2E) * la.y) + (ex2((ma.z - M) * LOG2E) * la.z + ex2((ma.w - M) * LOG2E) * la.w)
                          + (ex2((mb.x - M) * LOG2E) * lb.x + ex2((mb.y - M) * LOG2E) * lb.y) + (ex2((mb.z - M) * LOG2E) * lb.z + ex2((mb.w - M) * LOG2E) * lb.w);
            fin_scale = __fdividef(ex2((m_run - M) * LOG2E), L);
        }
        mbar_wait(bar_full + st * 8, ph);
        const uint32_t vb = v_base + st * STAGE_BYTES;
        {
            uint32_t relV = 0, pvV = 0;
#pragma unroll
            for (int j = 0; j < 8; j++) {
                uint32_t a[4];
                ldsm_x4_t(a, vb ^ (j << 4));
                mma_bf16((j & 1) ? acc1 : acc0, a, pp0 & msk[j], pp1 & msk[j]);
            }
            if (seq - (endgame ? 1 : 0) < NSEQ && lane == 0) {
                relV = atom_inc_shared(cnt_rel + st * 4);
                pvV = lds32(prog_s);
            }
            if (tid == NTHREADS - 32) asm volatile("red.relaxed.gpu.global.add.u32 [%0], 1;" :: "l"(&g_progress[0]) : "memory");
            if ((relV & (NCW - 1)) == NCW - 1) {
                if (endgame) {
                    pace(pvV, prog_base + (uint32_t)((it + 1) * N_ATT - (FK_LEAD_END)));
                    issue_kv(k_next, stK);
                }
                if (seq < NSEQ) issue_kv(v_next, st);
            }
        }
        __syncwarp();
        seq++;
        if (++st == NST) { st = 0; ph ^= 1; }
    }

    {
        float* o = red_s + warp * 128;
        o[16 * t + g]          = (acc0[0] + acc1[0]) * fin_scale;
        o[16 * t + 8 + g]      = (acc0[1] + acc1[1]) * fin_scale;
        o[64 + 16 * t + g]     = (acc0[2] + acc1[2]) * fin_scale;
        o[64 + 16 * t + 8 + g] = (acc0[3] + acc1[3]) * fin_scale;
    }
    __syncthreads();
    if (tid < DH) {
        float v[8];
#pragma unroll
        for (int w = 0; w < 8; w++) v[w] = red_s[w * 128 + tid];
        const float o = ((v[0] + v[1]) + (v[2] + v[3])) + ((v[4] + v[5]) + (v[6] + v[7]));
        o_s[((tid >> 1) & 3) * 32 + (tid >> 4) * 4 + ((tid >> 3) & 1) * 2 + (tid & 1)] = __float2bfloat16_rn(o);
    }
    __syncthreads();
    {
        float d[4][4];
#pragma unroll
        for (int j = 0; j < 4; j++) { d[j][0] = d[j][1] = d[j][2] = d[j][3] = 0.f; }
        uint4 ov[4];
#pragma unroll
        for (int i = 0; i < 4; i++) ov[i] = *reinterpret_cast<const uint4*>(o_s + t * 32 + i * 8);
#pragma unroll
        for (int i = 0; i < 4; i++) {
#pragma unroll
            for (int j = 0; j < 4; j++) mma_bf16(d[j], wa[2 * i][j], ov[i].x, ov[i].y);
#pragma unroll
            for (int j = 0; j < 4; j++) mma_bf16(d[j], wa[2 * i + 1][j], ov[i].z, ov[i].w);
        }
        float r0 = d[0][0], r1 = d[0][2];
        if (t == 1) { r0 = d[1][0]; r1 = d[1][2]; }
        if (t == 2) { r0 = d[2][0]; r1 = d[2][2]; }
        if (t == 3) { r0 = d[3][0]; r1 = d[3][2]; }
        st_relaxed(a_out, make_uint4(__float_as_uint(r0), tag, __float_as_uint(r1), tag));
    }
    if (warp == 0) {
        const uint4* p = &g_attn_part[((b * 32 + h) * NH + q4 * 8) * 8 + cp];
        uint4 v[8];
#pragma unroll
        for (int i = 0; i < 8; i++) v[i] = ld_relaxed(p + i * 8);
        for (int spin = 0; spin < (1 << 20); spin++) {
            bool ok = true;
#pragma unroll
            for (int i = 0; i < 8; i++) {
                if (!ll_valid(v[i], tag)) { v[i] = ld_relaxed(p + i * 8); ok = false; }
            }
            if (ok) break;
        }
        __syncwarp();
        float s0 = ((__uint_as_float(v[0].x) + __uint_as_float(v[1].x)) + (__uint_as_float(v[2].x) + __uint_as_float(v[3].x)))
                 + ((__uint_as_float(v[4].x) + __uint_as_float(v[5].x)) + (__uint_as_float(v[6].x) + __uint_as_float(v[7].x)));
        float s1 = ((__uint_as_float(v[0].z) + __uint_as_float(v[1].z)) + (__uint_as_float(v[2].z) + __uint_as_float(v[3].z)))
                 + ((__uint_as_float(v[4].z) + __uint_as_float(v[5].z)) + (__uint_as_float(v[6].z) + __uint_as_float(v[7].z)));
        s0 += __shfl_xor_sync(0xffffffffu, s0, 8);  s1 += __shfl_xor_sync(0xffffffffu, s1, 8);
        s0 += __shfl_xor_sync(0xffffffffu, s0, 16); s1 += __shfl_xor_sync(0xffffffffu, s1, 16);
        const float o0 = x0 + bf16r(bf16r(s0) * g0), o1 = x1 + bf16r(bf16r(s1) * g1);
        const int src = (2 * lane) & 7;
        const float a0 = __shfl_sync(0xffffffffu, o0, src), a1 = __shfl_sync(0xffffffffu, o0, src + 1);
        const float b0 = __shfl_sync(0xffffffffu, o1, src), b1 = __shfl_sync(0xffffffffu, o1, src + 1);
        if (lane < 8)
            *reinterpret_cast<uint32_t*>(out + b * DM + h * 16 + 2 * lane) = lane < 4 ? pack_bf16(a0, a1) : pack_bf16(b0, b1);
        if (lane == 0) { g_epoch[cta] = tag + 1; }
    }
}

}

extern "C" void kernel_launch(void* const* d_in, const int* in_sizes, int n_in, void* d_out, int out_size) {
    (void)in_sizes; (void)n_in; (void)out_size;
    const __nv_bfloat16* x  = (const __nv_bfloat16*)d_in[0];
    const __nv_bfloat16* Kc = (const __nv_bfloat16*)d_in[1];
    const __nv_bfloat16* Vc = (const __nv_bfloat16*)d_in[2];
    const __nv_bfloat16* wq = (const __nv_bfloat16*)d_in[3];
    const __nv_bfloat16* wo = (const __nv_bfloat16*)d_in[4];
    const __nv_bfloat16* w1 = (const __nv_bfloat16*)d_in[6];
    const __nv_bfloat16* w2 = (const __nv_bfloat16*)d_in[7];

    static bool attr_set = false;
    if (!attr_set) {
        cudaFuncSetAttribute(fk::fused_decode_kernel, cudaFuncAttributeMaxDynamicSharedMemorySize, fk::SMEM_BYTES);
        attr_set = true;
    }
    fk::fused_decode_kernel<<<fk::N_CTA, fk::NTHREADS, fk::SMEM_BYTES>>>(x, Kc, Vc, wq, wo, w1, w2, (__nv_bfloat16*)d_out);
}
```

```cpp
#include <cuda_runtime.h>
#include <cuda_bf16.h>
#include <stdint.h>

namespace fk {

#define FK_NST 4
#define FK_FIRST 2
#define FK_PRE 1
#define FK_XFIRST 0
#define FK_PF 0
#define FK_WTILE 4
#define FK_WSTEP 10
#define FK_LEAD 0
#define FK_ENDT 16
#define FK_LEAD_END 40

constexpr int NB = 4, NH = 32, SK = 8192, DH = 128, DM = 512, FF = 1376;
constexpr int TK = 128;
constexpr int NT = SK / TK;
constexpr int STAGE_BYTES = TK * DH * 2;
constexpr int NST = FK_NST;
constexpr int NCW = 8;
constexpr int NTHREADS = NCW * 32;
constexpr int N_ATT = NB * NH;
constexpr int N_FFN = 4;
constexpr int FS = FF / N_FFN;
constexpr int N_CTA = N_ATT + N_FFN;
constexpr int NSEQ = 2 * NT;
static_assert(NST % 2 == 0, "K tiles live in the even stages, V tiles in the odd ones");

constexpr int OFF_W   = NST * STAGE_BYTES;
constexpr int OFF_XN  = OFF_W;
constexpr int OFF_X   = OFF_W + 8192;
constexpr int OFF_RED = OFF_W + 12288;
constexpr int OFF_BAR = OFF_W + STAGE_BYTES;
constexpr int OFF_Q   = OFF_BAR + 256;
constexpr int OFF_ML  = OFF_Q + 256;
constexpr int OFF_O   = OFF_ML + 64;
constexpr int SMEM_ATT = OFF_O + 256;
constexpr int FFN_CHUNK = 64 * FS * 2;
constexpr int NBF = (NST >= 6) ? 4 : 2;
constexpr int FFN_XN = NBF * FFN_CHUNK, FFN_H = FFN_XN + 8192, FFN_RED = FFN_H + 5504, FFN_BAR = FFN_RED + 32768;
constexpr int SMEM_FFN = FFN_BAR + 64;
static_assert(FFN_CHUNK == 43 * DM * 2, "chunk geometry");
constexpr int SMEM_BYTES = SMEM_ATT > SMEM_FFN ? SMEM_ATT : SMEM_FFN;

__device__ __align__(256) uint4 g_q_part[NH * NB * 32];
__device__ __align__(256) uint4 g_attn_part[NB * 32 * NH * 8];
__device__ __align__(256) uint4 g_ffn_part[NB * 32 * N_FFN * 8];
__device__ __align__(256) uint32_t g_progress[64];
#define FK_ONE4 1u, 1u, 1u, 1u
#define FK_ONE16 FK_ONE4, FK_ONE4, FK_ONE4, FK_ONE4
#define FK_ONE64 FK_ONE16, FK_ONE16, FK_ONE16, FK_ONE16
__device__ __align__(256) uint32_t g_epoch[N_CTA] = {FK_ONE64, FK_ONE64, FK_ONE4};

__device__ __forceinline__ uint32_t smem_u32(const void* p) { return (uint32_t)__cvta_generic_to_shared(p); }

__device__ __forceinline__ void mbar_init(uint32_t bar, uint32_t cnt) {
    asm volatile("mbarrier.init.shared::cta.b64 [%0], %1;" :: "r"(bar), "r"(cnt) : "memory");
}
__device__ __forceinline__ void mbar_expect_tx(uint32_t bar, uint32_t bytes) {
    asm volatile("mbarrier.arrive.expect_tx.shared::cta.b64 _, [%0], %1;" :: "r"(bar), "r"(bytes) : "memory");
}
__device__ __forceinline__ uint32_t atom_inc_shared(uint32_t addr) {
    uint32_t old;
    asm volatile("atom.relaxed.cta.shared::cta.add.u32 %0, [%1], 1;" : "=r"(old) : "r"(addr) : "memory");
    return old;
}
__device__ __forceinline__ void mbar_wait(uint32_t bar, uint32_t parity) {
    asm volatile(
        "{\n"
        ".reg .pred p;\n"
        "FK_WAIT:\n"
        "mbarrier.try_wait.parity.shared::cta.b64 p, [%0], %1;\n"
        "@p bra FK_DONE;\n"
        "bra FK_WAIT;\n"
        "FK_DONE:\n"
        "}\n" :: "r"(bar), "r"(parity) : "memory");
}
__device__ __forceinline__ void bulk_load(uint32_t dst, const void* src, uint32_t bytes, uint32_t bar, uint64_t pol) {
    asm volatile("cp.async.bulk.shared::cluster.global.mbarrier::complete_tx::bytes.L2::cache_hint [%0], [%1], %2, [%3], %4;"
                 :: "r"(dst), "l"(src), "r"(bytes), "r"(bar), "l"(pol) : "memory");
}
__device__ __forceinline__ uint4 ldg_nc(const void* p) {
    uint4 v;
    asm volatile("ld.global.nc.L1::no_allocate.v4.u32 {%0,%1,%2,%3}, [%4];"
                 : "=r"(v.x), "=r"(v.y), "=r"(v.z), "=r"(v.w) : "l"(p));
    return v;
}
__device__ __forceinline__ void bulk_load_plain(uint32_t dst, const void* src, uint32_t bytes, uint32_t bar) {
    asm volatile("cp.async.bulk.shared::cluster.global.mbarrier::complete_tx::bytes [%0], [%1], %2, [%3];"
                 :: "r"(dst), "l"(src), "r"(bytes), "r"(bar) : "memory");
}
__device__ __forceinline__ uint32_t ldg_nc32(const void* p) {
    uint32_t v;
    asm volatile("ld.global.nc.L1::no_allocate.u32 %0, [%1];" : "=r"(v) : "l"(p));
    return v;
}
__device__ __forceinline__ uint32_t lds32(uint32_t addr) {
    uint32_t v;
    asm volatile("ld.volatile.shared.u32 %0, [%1];" : "=r"(v) : "r"(addr) : "memory");
    return v;
}
__device__ __forceinline__ uint32_t pin(uint32_t v) {
    uint32_t r;
    asm volatile("mov.b32 %0, %1;" : "=r"(r) : "r"(v));
    return r;
}
__device__ __forceinline__ uint32_t ld_relaxed32(const uint32_t* p) {
    uint32_t v;
    asm volatile("ld.relaxed.gpu.global.u32 %0, [%1];" : "=r"(v) : "l"(p) : "memory");
    return v;
}
__device__ __forceinline__ bool mbar_test(uint32_t bar, uint32_t parity) {
    uint32_t ok;
    asm volatile("{\n.reg .pred p;\nmbarrier.test_wait.parity.shared::cta.b64 p, [%1], %2;\nselp.u32 %0, 1, 0, p;\n}\n"
                 : "=r"(ok) : "r"(bar), "r"(parity) : "memory");
    return ok != 0;
}
__device__ __forceinline__ uint4 ld_relaxed(const uint4* p) {
    uint4 v;
    asm volatile("ld.relaxed.gpu.global.v4.u32 {%0,%1,%2,%3}, [%4];"
                 : "=r"(v.x), "=r"(v.y), "=r"(v.z), "=r"(v.w) : "l"(p) : "memory");
    return v;
}
__device__ __forceinline__ void st_relaxed(uint4* p, uint4 v) {
    asm volatile("st.relaxed.gpu.global.v4.u32 [%0], {%1,%2,%3,%4};"
                 :: "l"(p), "r"(v.x), "r"(v.y), "r"(v.z), "r"(v.w) : "memory");
}
__device__ __forceinline__ void ldsm_x4(uint32_t (&r)[4], uint32_t addr) {
    asm volatile("ldmatrix.sync.aligned.m8n8.x4.shared.b16 {%0,%1,%2,%3}, [%4];"
                 : "=r"(r[0]), "=r"(r[1]), "=r"(r[2]), "=r"(r[3]) : "r"(addr) : "memory");
}
__device__ __forceinline__ void ldsm_x4_t(uint32_t (&r)[4], uint32_t addr) {
    asm volatile("ldmatrix.sync.aligned.m8n8.x4.trans.shared.b16 {%0,%1,%2,%3}, [%4];"
                 : "=r"(r[0]), "=r"(r[1]), "=r"(r[2]), "=r"(r[3]) : "r"(addr) : "memory");
}
__device__ __forceinline__ void mma_bf16(float (&c)[4], const uint32_t (&a)[4], uint32_t b0, uint32_t b1) {
    asm volatile("mma.sync.aligned.m16n8k16.row.col.f32.bf16.bf16.f32 {%0,%1,%2,%3}, {%4,%5,%6,%7}, {%8,%9}, {%0,%1,%2,%3};"
                 : "+f"(c[0]), "+f"(c[1]), "+f"(c[2]), "+f"(c[3])
                 : "r"(a[0]), "r"(a[1]), "r"(a[2]), "r"(a[3]), "r"(b0), "r"(b1));
}
__device__ __forceinline__ float ex2(float x) {
    float r;
    asm("ex2.approx.ftz.f32 %0, %1;" : "=f"(r) : "f"(x));
    return r;
}
__device__ __forceinline__ uint32_t pack_bf16(float lo, float hi) {
    uint32_t r;
    asm("cvt.rn.bf16x2.f32 %0, %1, %2;" : "=r"(r) : "f"(hi), "f"(lo));
    return r;
}
__device__ __forceinline__ float bf_lo(uint32_t w) { return __uint_as_float(w << 16); }
__device__ __forceinline__ float bf_hi(uint32_t w) { return __uint_as_float(w & 0xffff0000u); }
__device__ __forceinline__ float bf16r(float x) { return __bfloat162float(__float2bfloat16_rn(x)); }
__device__ __forceinline__ float silu_f(float x) { return x / (1.0f + __expf(-x)); }

__device__ __forceinline__ void warp_layernorm(const uint4 a, const uint4 b, float (&xn)[16]) {
    float v[16];
    v[0] = bf_lo(a.x); v[1] = bf_hi(a.x); v[2] = bf_lo(a.y); v[3] = bf_hi(a.y);
    v[4] = bf_lo(a.z); v[5] = bf_hi(a.z); v[6] = bf_lo(a.w); v[7] = bf_hi(a.w);
    v[8] = bf_lo(b.x); v[9] = bf_hi(b.x); v[10] = bf_lo(b.y); v[11] = bf_hi(b.y);
    v[12] = bf_lo(b.z); v[13] = bf_hi(b.z); v[14] = bf_lo(b.w); v[15] = bf_hi(b.w);
    float s = 0.f;
#pragma unroll
    for (int i = 0; i < 16; i++) s += v[i];
#pragma unroll
    for (int o = 16; o; o >>= 1) s += __shfl_xor_sync(0xffffffffu, s, o);
    const float mean = s * (1.0f / DM);
    float ss = 0.f;
#pragma unroll
    for (int i = 0; i < 16; i++) { const float d = v[i] - mean; ss = fmaf(d, d, ss); }
#pragma unroll
    for (int o = 16; o; o >>= 1) ss += __shfl_xor_sync(0xffffffffu, ss, o);
    const float m_bf = bf16r(mean);
    const float den = bf16r(sqrtf(bf16r(bf16r(ss * (1.0f / DM)) + 1e-5f)));
#pragma unroll
    for (int i = 0; i < 16; i++) xn[i] = bf16r(__fdiv_rn(bf16r(v[i] - m_bf), den));
}

__device__ __forceinline__ bool ll_valid(const uint4& v, uint32_t tag) { return v.y == tag && v.w == tag; }

__device__ __forceinline__ void ffn_cta(uint8_t* smem, int f, uint32_t tag,
                                        const __nv_bfloat16* __restrict__ x,
                                        const __nv_bfloat16* __restrict__ w1,
                                        const __nv_bfloat16* __restrict__ w2) {
    const int tid = threadIdx.x, warp = tid >> 5, lane = tid & 31;
    const uint32_t sbase = smem_u32(smem), bar = sbase + FFN_BAR;
    float* xnT = reinterpret_cast<float*>(smem + FFN_XN);
    float* hT  = reinterpret_cast<float*>(smem + FFN_H);
    float* red = reinterpret_cast<float*>(smem + FFN_RED);
    if (tid == 0) {
#pragma unroll
        for (int s = 0; s < NBF; s++) mbar_init(bar + s * 8, 1);
    }
    __syncthreads();
    auto issue = [&](int c) {
        const int s = c % NBF;
        if (tid == 0) mbar_expect_tx(bar + s * 8, FFN_CHUNK);
        if (c < 8) {
            __syncthreads();
            if (tid < 64) bulk_load_plain(sbase + s * FFN_CHUNK + tid * (FS * 2), w1 + (size_t)(c * 64 + tid) * FF + f * FS, FS * 2, bar + s * 8);
        } else if (tid == 0) {
            bulk_load_plain(sbase + s * FFN_CHUNK, w2 + (size_t)(f * FS + (c - 8) * 43) * DM, FFN_CHUNK, bar + s * 8);
        }
    };
    for (int c = 0; c < NBF; c++) issue(c);
    if (warp < NB) {
        float xn[16];
        const uint4 xa = ldg_nc(x + warp * DM + lane * 16), xb = ldg_nc(x + warp * DM + lane * 16 + 8);
        warp_layernorm(xa, xb, xn);
#pragma unroll
        for (int i = 0; i < 16; i++) xnT[(lane * 16 + i) * 4 + warp] = xn[i];
    }
    __syncthreads();
    float acc[4][8];
#pragma unroll
    for (int b = 0; b < 4; b++)
#pragma unroll
        for (int c = 0; c < 8; c++) acc[b][c] = 0.f;
#pragma unroll 1
    for (int c = 0; c < 16; c++) {
        const int s = c % NBF;
        mbar_wait(bar + s * 8, (c / NBF) & 1);
        const bool st1 = c < 8;
        const int cg = st1 ? tid % 43 : (tid & 63), r0 = st1 ? tid / 43 : (tid >> 6);
        const int rstep = st1 ? 5 : 4, nrows = st1 ? 64 : 43, rbytes = st1 ? FS * 2 : DM * 2;
        const float* vec = st1 ? xnT + c * 64 * 4 : hT + (c - 8) * 43 * 4;
        const uint8_t* wb = smem + s * FFN_CHUNK + cg * 16;
        if (!st1 || tid < 43 * 5) {
#pragma unroll 2
            for (int k = r0; k < nrows; k += rstep) {
                const uint4 w = *reinterpret_cast<const uint4*>(wb + k * rbytes);
                const float4 xv = *reinterpret_cast<const float4*>(vec + k * 4);
                const float wf[8] = {bf_lo(w.x), bf_hi(w.x), bf_lo(w.y), bf_hi(w.y), bf_lo(w.z), bf_hi(w.z), bf_lo(w.w), bf_hi(w.w)};
#pragma unroll
                for (int j = 0; j < 8; j++) {
                    acc[0][j] = fmaf(xv.x, wf[j], acc[0][j]);
                    acc[1][j] = fmaf(xv.y, wf[j], acc[1][j]);
                    acc[2][j] = fmaf(xv.z, wf[j], acc[2][j]);
                    acc[3][j] = fmaf(xv.w, wf[j], acc[3][j]);
                }
            }
        }
        __syncthreads();
        if (c + NBF < 16) issue(c + NBF);
        if (c == 7) {
            if (tid < 43 * 5) {
#pragma unroll
                for (int b = 0; b < 4; b++)
#pragma unroll
                    for (int j = 0; j < 8; j++) red[(r0 * 4 + b) * FS + cg * 8 + j] = acc[b][j];
            }
#pragma unroll
            for (int b = 0; b < 4; b++)
#pragma unroll
                for (int j = 0; j < 8; j++) acc[b][j] = 0.f;
            __syncthreads();
            for (int i = tid; i < 4 * FS; i += NTHREADS) {
                const int b = i / FS, cc = i % FS;
                float sum = 0.f;
#pragma unroll
                for (int ks = 0; ks < 5; ks++) sum += red[(ks * 4 + b) * FS + cc];
                hT[cc * 4 + b] = bf16r(silu_f(bf16r(sum)));
            }
            __syncthreads();
        }
    }
    {
        const int cg = tid & 63, fs = tid >> 6;
#pragma unroll
        for (int b = 0; b < 4; b++)
#pragma unroll
            for (int j = 0; j < 8; j++) red[(fs * 4 + b) * DM + cg * 8 + j] = acc[b][j];
    }
    __syncthreads();
    for (int i = tid; i < NB * 256; i += NTHREADS) {
        const int b = i >> 8, j = (i >> 3) & 31, p = i & 7;
        float s0 = 0.f, s1 = 0.f;
#pragma unroll
        for (int fs = 0; fs < 4; fs++) { s0 += red[(fs * 4 + b) * DM + 16 * j + p]; s1 += red[(fs * 4 + b) * DM + 16 * j + 8 + p]; }
        st_relaxed(&g_ffn_part[((b * 32 + j) * N_FFN + f) * 8 + p],
                   make_uint4(__float_as_uint(s0), tag, __float_as_uint(s1), tag));
    }
}

__global__ void __launch_bounds__(NTHREADS, 1)
fused_decode_kernel(const __nv_bfloat16* __restrict__ x, const __nv_bfloat16* __restrict__ Kc,
                    const __nv_bfloat16* __restrict__ Vc, const __nv_bfloat16* __restrict__ wq,
                    const __nv_bfloat16* __restrict__ wo, const __nv_bfloat16* __restrict__ w1,
                    const __nv_bfloat16* __restrict__ w2, __nv_bfloat16* __restrict__ out) {
    extern __shared__ __align__(1024) uint8_t smem[];
    const int cta = blockIdx.x;
    const int tid = threadIdx.x, warp = tid >> 5, lane = tid & 31;
    if (cta >= N_ATT) {
        const uint32_t tag = ld_relaxed32(&g_epoch[cta]);
        ffn_cta(smem, cta - N_ATT, tag, x, w1, w2);
        if (tid == 0) { g_epoch[cta] = tag + 1; }
        return;
    }

    const int b = cta & 3, h = cta >> 2;
    const int bh = b * NH + h;
    const uint32_t sbase = pin(smem_u32(smem));
    const uint32_t bar_full = sbase + OFF_BAR;
    const uint32_t cnt_rel = bar_full + NST * 8;
    const char* kp = reinterpret_cast<const char*>(Kc) + (size_t)bh * SK * DH * 2;
    const char* vp = reinterpret_cast<const char*>(Vc) + (size_t)bh * SK * DH * 2;
    const char* wop = reinterpret_cast<const char*>(wo) + (size_t)h * DH * DM * 2;
    uint64_t pol;
    asm volatile("createpolicy.fractional.L2::evict_first.b64 %0, 1.0;" : "=l"(pol));
    auto issue_kv = [&](const char* src, int s) {
        const uint32_t bar = bar_full + s * 8;
        mbar_expect_tx(bar, STAGE_BYTES);
        bulk_load(sbase + s * STAGE_BYTES, src, STAGE_BYTES, bar, pol);
    };
    auto issue_first = [&](int n) { issue_kv(((n & 1) ? vp : kp) + (size_t)(n >> 1) * STAGE_BYTES, n); };
    const uint32_t bar_w = bar_full + 216, cnt_w = bar_full + 224;
    auto issue_w = [&](int q) {
        mbar_expect_tx(bar_w, STAGE_BYTES);
        bulk_load_plain(sbase + OFF_W, wop + (size_t)q * STAGE_BYTES, STAGE_BYTES, bar_w);
    };

    const int g = lane >> 2, t = lane & 3;
    float* xn_s  = reinterpret_cast<float*>(smem + OFF_XN);
    float* red_s = reinterpret_cast<float*>(smem + OFF_RED);
    __nv_bfloat16* q_s = reinterpret_cast<__nv_bfloat16*>(smem + OFF_Q);
    float* ml_s = reinterpret_cast<float*>(smem + OFF_ML);
    __nv_bfloat16* o_s = reinterpret_cast<__nv_bfloat16*>(smem + OFF_O);

    uint4* const q_out = &g_q_part[(h * NB + (lane >> 3)) * 32 + b * 8 + (lane & 7)];
    uint4* const a_out = &g_attn_part[((b * 32 + warp * 4 + t) * NH + h) * 8 + g];

    volatile uint32_t* q_flag = reinterpret_cast<volatile uint32_t*>(smem + OFF_BAR + 192);
    const uint32_t bar_x = bar_full + 200;
    if (tid == 0) {
        mbar_init(bar_full, 1);
        issue_first(0);
        mbar_init(bar_x, 1);
        mbar_expect_tx(bar_x, NB * DM * 2);
        bulk_load_plain(sbase + OFF_X, x, NB * DM * 2, bar_x);
#pragma unroll
        for (int s = 1; s < NST; s++) mbar_init(bar_full + s * 8, 1);
        mbar_init(bar_w, 1);
#pragma unroll
        for (int s = 0; s < NST; s++) *reinterpret_cast<volatile uint32_t*>(smem + OFF_BAR + NST * 8 + s * 4) = 0;
        *reinterpret_cast<volatile uint32_t*>(smem + OFF_BAR + 224) = 0;
        *q_flag = 0;
#pragma unroll 1
        for (int s = 1; s < FK_PRE; s++) issue_first(s);
    }
    uint32_t qf[8][2];
    uint32_t tag;
    {
        uint32_t w[32];
        const __nv_bfloat16* wp = wq + (size_t)(warp * 64 + (lane >> 4) * 32) * (NH * DH) + h * DH + b * 32 + (lane & 15) * 2;
#pragma unroll
        for (int i = 0; i < 32; i++) w[i] = ldg_nc32(wp + (size_t)i * (NH * DH));
        tag = ld_relaxed32(&g_epoch[cta]);
        if (tid == 0) {
#pragma unroll 1
            for (int s = FK_PRE; s < FK_FIRST; s++) issue_first(s);
            asm volatile("prefetch.global.L2 [%0];" :: "l"(wop));
        }
        if (warp == 0) st_relaxed(q_out, make_uint4(0, 0, 0, 0));
        st_relaxed(a_out, make_uint4(0, 0, 0, 0));
        __syncthreads();
        if (warp < 4) {
            float xn[16];
            mbar_wait(bar_x, 0);
            const uint4 xa = *reinterpret_cast<const uint4*>(smem + OFF_X + warp * DM * 2 + lane * 32);
            const uint4 xb = *reinterpret_cast<const uint4*>(smem + OFF_X + warp * DM * 2 + lane * 32 + 16);
            warp_layernorm(xa, xb, xn);
#pragma unroll
            for (int i = 0; i < 16; i += 4)
                *reinterpret_cast<float4*>(xn_s + warp * DM + lane * 16 + i) = make_float4(xn[i], xn[i + 1], xn[i + 2], xn[i + 3]);
        }
        __syncthreads();
        float acc[4][2];
#pragma unroll
        for (int bb = 0; bb < 4; bb++) acc[bb][0] = acc[bb][1] = 0.f;
        const float* xp = xn_s + warp * 64 + (lane >> 4) * 32;
#pragma unroll
        for (int i4 = 0; i4 < 8; i4++) {
#pragma unroll
            for (int bb = 0; bb < 4; bb++) {
                const float4 xv = *reinterpret_cast<const float4*>(xp + bb * DM + i4 * 4);
                const float xs[4] = {xv.x, xv.y, xv.z, xv.w};
#pragma unroll
                for (int u = 0; u < 4; u++) {
                    acc[bb][0] = fmaf(xs[u], bf_lo(w[i4 * 4 + u]), acc[bb][0]);
                    acc[bb][1] = fmaf(xs[u], bf_hi(w[i4 * 4 + u]), acc[bb][1]);
                }
            }
        }
        const bool up = lane >= 16;
        float k0 = up ? acc[2][0] : acc[0][0], k1 = up ? acc[2][1] : acc[0][1];
        float k2 = up ? acc[3][0] : acc[1][0], k3 = up ? acc[3][1] : acc[1][1];
        k0 += __shfl_xor_sync(0xffffffffu, up ? acc[0][0] : acc[2][0], 16);
        k1 += __shfl_xor_sync(0xffffffffu, up ? acc[0][1] : acc[2][1], 16);
        k2 += __shfl_xor_sync(0xffffffffu, up ? acc[1][0] : acc[3][0], 16);
        k3 += __shfl_xor_sync(0xffffffffu, up ? acc[1][1] : acc[3][1], 16);
        float* rp = red_s + warp * 128 + (up ? 64 : 0) + (lane & 15) * 2;
        *reinterpret_cast<float2*>(rp)      = make_float2(k0, k1);
        *reinterpret_cast<float2*>(rp + 32) = make_float2(k2, k3);
        __syncthreads();
        if (warp == 0) {
            float4 s = make_float4(0.f, 0.f, 0.f, 0.f);
#pragma unroll
            for (int w8 = 0; w8 < NCW; w8++) {
                const float4 v = *reinterpret_cast<const float4*>(red_s + w8 * 128 + lane * 4);
                s.x += v.x; s.y += v.y; s.z += v.z; s.w += v.w;
            }
            st_relaxed(q_out, make_uint4(pack_bf16(s.x, s.y), tag, pack_bf16(s.z, s.w), tag));
            const uint4* p = &g_q_part[(h * NB + b) * 32 + lane];
            uint4 v = ld_relaxed(p);
            for (int spin = 0; !ll_valid(v, tag) && spin < (1 << 20); spin++) v = ld_relaxed(p);
            *reinterpret_cast<uint2*>(q_s + lane * 4) = make_uint2(v.x, v.z);
            if (lane == 0) *q_flag = 1;
        }
        if (tid == NTHREADS - 32) {
            int next = FK_FIRST, watch = 0;
            while (next < NST + FK_PF) {
                if (mbar_test(bar_full + watch * 8, 0)) {
                    if (next < NST) issue_first(next);
                    else
                        asm volatile("cp.async.bulk.prefetch.L2.global [%0], %1;"
                                     :: "l"(((next & 1) ? vp : kp) + (size_t)(next >> 1) * STAGE_BYTES), "r"(STAGE_BYTES) : "memory");
                    next++; watch++;
                } else if (*q_flag) break;
            }
#pragma unroll 1
            for (; next < NST; next++) issue_first(next);
        }
        __syncthreads();
#pragma unroll
        for (int j = 0; j < 8; j++) {
            const int c = (j ^ g) & 7;
            qf[j][0] = *reinterpret_cast<const uint32_t*>(q_s + c * 8 + 2 * t);
            qf[j][1] = *reinterpret_cast<const uint32_t*>(q_s + 64 + c * 8 + 2 * t);
        }
    }

    constexpr float RSQRT_DH = 0.08838834764831845f, LOG2E = 1.4426950408889634f;
    const int li = lane & 7, lm = lane >> 3;
    const uint32_t k_base = pin(sbase + (uint32_t)((warp * 16 + li + 8 * (lm & 1)) * 256 + (lm >> 1) * 128 + li * 16));
    const uint32_t v_base = pin(sbase + (uint32_t)((warp * 16 + li + 8 * (lm >> 1)) * 256 + (lm & 1) * 128 + li * 16));
    const bool diag = (t == (g >> 1));
    uint32_t msk[8];
#pragma unroll
    for (int j = 0; j < 8; j++) msk[j] = pin((j == (g ^ (2 * t)) ? 0x0000ffffu : 0u) | (j == (g ^ (2 * t) ^ 1) ? 0xffff0000u : 0u));
    const uint32_t ones[4] = {0x3f803f80u, 0x3f803f80u, 0x3f803f80u, 0x3f803f80u};

    float acc0[4] = {0.f, 0.f, 0.f, 0.f}, acc1[4] = {0.f, 0.f, 0.f, 0.f}, lacc[4] = {0.f, 0.f, 0.f, 0.f};
    float m_raw = -INFINITY;
    float m_run = -INFINITY, mc = 0.f;
    float fin_scale = 0.f;
    int st = 0; uint32_t ph = 0;
    int seq = NST;
    uint32_t wa[8][4][4];
    float g0 = 0.f, g1 = 0.f;
    uint4 gv = make_uint4(0, 0, 0, 0);
    const int cp = lane & 7, q4 = lane >> 3;
    const float x0 = __bfloat162float(reinterpret_cast<const __nv_bfloat16*>(smem + OFF_X)[b * DM + h * 16 + cp]);
    const float x1 = __bfloat162float(reinterpret_cast<const __nv_bfloat16*>(smem + OFF_X)[b * DM + h * 16 + 8 + cp]);
    const uint32_t prog_base = (tag - 1) * (uint32_t)(N_ATT * NT);
    const uint32_t prog_s = bar_full + 208;
    uint32_t prog_v = prog_base;
    if (tid == 0) *reinterpret_cast<volatile uint32_t*>(smem + OFF_BAR + 208) = prog_base;
    __syncthreads();
    auto pace = [&](uint32_t pv, uint32_t lim) {
        for (int spin = 0; (int)(pv - lim) < 0 && spin < 4096; spin++) pv = ld_relaxed32(&g_progress[0]);
    };

#pragma unroll 1
    for (int it = 0; it < NT; it++) {
#pragma unroll
        for (int q = 0; q <= 4; q++) {
            if (it == FK_WTILE + q * FK_WSTEP) {
                if (q == 0) {
                    if (tid == 0) {
                        asm volatile("fence.proxy.async.shared::cta;" ::: "memory");
                        issue_w(0);
                    }
                } else {
                    mbar_wait(bar_w, (q - 1) & 1);
                    const uint32_t wb = sbase + OFF_W + (li + 8 * (lane >> 4)) * 1024 + warp * 128 + (lm & 1) * 16;
#pragma unroll
                    for (int j = 0; j < 4; j++) {
                        ldsm_x4_t(wa[2 * q - 2][j], wb + j * 32);
                        ldsm_x4_t(wa[2 * q - 1][j], wb + 16384 + j * 32);
                    }
                    if (q < 4 && lane == 0) {
                        const uint32_t rel = atom_inc_shared(cnt_w);
                        if ((rel & (NCW - 1)) == NCW - 1) issue_w(q);
                    }
                }
                __syncwarp();
            }
        }
        if (it == NT - 12 && warp == 0) {
            gv = ld_relaxed(&g_ffn_part[((b * 32 + h) * N_FFN + q4) * 8 + cp]);
        }
        if (it == NT - 2 && warp == 0) {
            const uint4* p = &g_ffn_part[((b * 32 + h) * N_FFN + q4) * 8 + cp];
            uint4 v = gv;
            for (int spin = 0; !ll_valid(v, tag) && spin < (1 << 20); spin++) { __nanosleep(64); v = ld_relaxed(p); }
            __syncwarp();
            g0 = __uint_as_float(v.x); g1 = __uint_as_float(v.z);
            g0 += __shfl_xor_sync(0xffffffffu, g0, 8);  g1 += __shfl_xor_sync(0xffffffffu, g1, 8);
            g0 += __shfl_xor_sync(0xffffffffu, g0, 16); g1 += __shfl_xor_sync(0xffffffffu, g1, 16);
            g0 = bf16r(silu_f(bf16r(g0))); g1 = bf16r(silu_f(bf16r(g1)));
        }
        if (tid == 0) {
            *reinterpret_cast<volatile uint32_t*>(smem + OFF_BAR + 208) = prog_v;
            prog_v = ld_relaxed32(&g_progress[0]);
        }
        const bool endgame = it >= NT - FK_ENDT;
        const char* k_next = kp + (size_t)(it + NST / 2) * STAGE_BYTES;
        const char* v_next = vp + (size_t)(it + NST / 2) * STAGE_BYTES;
        mbar_wait(bar_full + st * 8, ph);
        float c0[4] = {0.f, 0.f, 0.f, 0.f}, c1[4] = {0.f, 0.f, 0.f, 0.f};
        uint32_t relK = 0, pvK = 0;
        const uint32_t kb = k_base + st * STAGE_BYTES;
        {
#pragma unroll
            for (int j = 0; j < 8; j++) {
                uint32_t a[4];
                ldsm_x4(a, kb ^ (j << 4));
                mma_bf16((j & 1) ? c1 : c0, a, qf[j][0], qf[j][1]);
            }
            if (!endgame && seq < NSEQ && lane == 0) {
                relK = atom_inc_shared(cnt_rel + st * 4);
                pvK = lds32(prog_s);
            }
        }
        const float u0 = (g & 1) ? (c0[1] + c1[1]) : (c0[0] + c1[0]);
        const float u1 = (g & 1) ? (c0[3] + c1[3]) : (c0[2] + c1[2]);
        int key = __float_as_int(diag ? fmaxf(u0, u1) : -INFINITY);
        key ^= (key >> 31) & 0x7fffffff;
        key = __reduce_max_sync(0xffffffffu, key);
        const uint32_t r1 = pack_bf16(u0, u1);
        const uint32_t r2 = pack_bf16(bf_lo(r1) * RSQRT_DH, bf_hi(r1) * RSQRT_DH);
        const float s0 = diag ? bf_lo(r2) : -INFINITY, s1 = diag ? bf_hi(r2) : -INFINITY;
        key ^= (key >> 31) & 0x7fffffff;
        const float tmax = __int_as_float(key);
        if (tmax > m_raw) {
            m_raw = tmax;
            const float m_new = bf16r(bf16r(tmax) * RSQRT_DH);
            const float sc = ex2((m_run - m_new) * LOG2E);
#pragma unroll
            for (int i = 0; i < 4; i++) { acc0[i] *= sc; acc1[i] *= sc; }
            lacc[0] *= sc;
            m_run = m_new;
            mc = -m_new * LOG2E;
        }
        const uint32_t pk = pack_bf16(ex2(fmaf(s0, LOG2E, mc)), ex2(fmaf(s1, LOG2E, mc)));
        const uint32_t xx = __shfl_sync(0xffffffffu, pk, 9 * t), yy = __shfl_sync(0xffffffffu, pk, 9 * t + 4);
        const uint32_t pp0 = __byte_perm(xx, yy, 0x5410), pp1 = __byte_perm(xx, yy, 0x7632);
        if ((relK & (NCW - 1)) == NCW - 1) {
            pace(pvK, prog_base + (uint32_t)(it * N_ATT - (FK_LEAD)));
            issue_kv(k_next, st);
        }
        __syncwarp();
        const int stK = st;
        seq++;
        if (++st == NST) { st = 0; ph ^= 1; }
        mma_bf16(lacc, ones, pp0, pp1);
        if (it == NT - 1) {
            if (lane == 0) { ml_s[warp] = m_run; ml_s[8 + warp] = lacc[0]; }
            __syncthreads();
            const float4 ma = *reinterpret_cast<const float4*>(ml_s), mb = *reinterpret_cast<const float4*>(ml_s + 4);
            const float4 la = *reinterpret_cast<const float4*>(ml_s + 8), lb = *reinterpret_cast<const float4*>(ml_s + 12);
            const float M = fmaxf(fmaxf(fmaxf(ma.x, ma.y), fmaxf(ma.z, ma.w)), fmaxf(fmaxf(mb.x, mb.y), fmaxf(mb.z, mb.w)));
            const float L = (ex2((ma.x - M) * LOG2E) * la.x + ex2((ma.y - M) * LOG2E) * la.y) + (ex2((ma.z - M) * LOG2E) * la.z + ex2((ma.w - M) * LOG2E) * la.w)
                          + (ex2((mb.x - M) * LOG2E) * lb.x + ex2((mb.y - M) * LOG2E) * lb.y) + (ex2((mb.z - M) * LOG2E) * lb.z + ex2((mb.w - M) * LOG2E) * lb.w);
            fin_scale = __fdividef(ex2((m_run - M) * LOG2E), L);
        }
        mbar_wait(bar_full + st * 8, ph);
        const uint32_t vb = v_base + st * STAGE_BYTES;
        {
            uint32_t relV = 0, pvV = 0;
#pragma unroll
            for (int j = 0; j < 8; j++) {
                uint32_t a[4];
                ldsm_x4_t(a, vb ^ (j << 4));
                mma_bf16((j & 1) ? acc1 : acc0, a, pp0 & msk[j], pp1 & msk[j]);
            }
            if (seq - (endgame ? 1 : 0) < NSEQ && lane == 0) {
                relV = atom_inc_shared(cnt_rel + st * 4);
                pvV = lds32(prog_s);
            }
            if (tid == NTHREADS - 32) asm volatile("red.relaxed.gpu.global.add.u32 [%0], 1;" :: "l"(&g_progress[0]) : "memory");
            if ((relV & (NCW - 1)) == NCW - 1) {
                if (endgame) {
                    pace(pvV, prog_base + (uint32_t)((it + 1) * N_ATT - (FK_LEAD_END)));
                    issue_kv(k_next, stK);
                }
                if (seq < NSEQ) issue_kv(v_next, st);
            }
        }
        __syncwarp();
        seq++;
        if (++st == NST) { st = 0; ph ^= 1; }
    }

    {
        float* o = red_s + warp * 128;
        o[16 * t + g]          = (acc0[0] + acc1[0]) * fin_scale;
        o[16 * t + 8 + g]      = (acc0[1] + acc1[1]) * fin_scale;
        o[64 + 16 * t + g]     = (acc0[2] + acc1[2]) * fin_scale;
        o[64 + 16 * t + 8 + g] = (acc0[3] + acc1[3]) * fin_scale;
    }
    __syncthreads();
    if (tid < DH) {
        float v[8];
#pragma unroll
        for (int w = 0; w < 8; w++) v[w] = red_s[w * 128 + tid];
        const float o = ((v[0] + v[1]) + (v[2] + v[3])) + ((v[4] + v[5]) + (v[6] + v[7]));
        o_s[((tid >> 1) & 3) * 32 + (tid >> 4) * 4 + ((tid >> 3) & 1) * 2 + (tid & 1)] = __float2bfloat16_rn(o);
    }
    __syncthreads();
    {
        float d[4][4];
#pragma unroll
        for (int j = 0; j < 4; j++) { d[j][0] = d[j][1] = d[j][2] = d[j][3] = 0.f; }
        uint4 ov[4];
#pragma unroll
        for (int i = 0; i < 4; i++) ov[i] = *reinterpret_cast<const uint4*>(o_s + t * 32 + i * 8);
#pragma unroll
        for (int i = 0; i < 4; i++) {
#pragma unroll
            for (int j = 0; j < 4; j++) mma_bf16(d[j], wa[2 * i][j], ov[i].x, ov[i].y);
#pragma unroll
            for (int j = 0; j < 4; j++) mma_bf16(d[j], wa[2 * i + 1][j], ov[i].z, ov[i].w);
        }
        float r0 = d[0][0], r1 = d[0][2];
        if (t == 1) { r0 = d[1][0]; r1 = d[1][2]; }
        if (t == 2) { r0 = d[2][0]; r1 = d[2][2]; }
        if (t == 3) { r0 = d[3][0]; r1 = d[3][2]; }
        st_relaxed(a_out, make_uint4(__float_as_uint(r0), tag, __float_as_uint(r1), tag));
    }
    if (warp == 0) {
        const uint4* p = &g_attn_part[((b * 32 + h) * NH + q4 * 8) * 8 + cp];
        uint4 v[8];
#pragma unroll
        for (int i = 0; i < 8; i++) v[i] = ld_relaxed(p + i * 8);
        for (int spin = 0; spin < (1 << 20); spin++) {
            bool ok = true;
#pragma unroll
            for (int i = 0; i < 8; i++) {
                if (!ll_valid(v[i], tag)) { v[i] = ld_relaxed(p + i * 8); ok = false; }
            }
            if (ok) break;
        }
        __syncwarp();
        float s0 = ((__uint_as_float(v[0].x) + __uint_as_float(v[1].x)) + (__uint_as_float(v[2].x) + __uint_as_float(v[3].x)))
                 + ((__uint_as_float(v[4].x) + __uint_as_float(v[5].x)) + (__uint_as_float(v[6].x) + __uint_as_float(v[7].x)));
        float s1 = ((__uint_as_float(v[0].z) + __uint_as_float(v[1].z)) + (__uint_as_float(v[2].z) + __uint_as_float(v[3].z)))
                 + ((__uint_as_float(v[4].z) + __uint_as_float(v[5].z)) + (__uint_as_float(v[6].z) + __uint_as_float(v[7].z)));
        s0 += __shfl_xor_sync(0xffffffffu, s0, 8);  s1 += __shfl_xor_sync(0xffffffffu, s1, 8);
        s0 += __shfl_xor_sync(0xffffffffu, s0, 16); s1 += __shfl_xor_sync(0xffffffffu, s1, 16);
        const float o0 = x0 + bf16r(bf16r(s0) * g0), o1 = x1 + bf16r(bf16r(s1) * g1);
        const int src = (2 * lane) & 7;
        const float a0 = __shfl_sync(0xffffffffu, o0, src), a1 = __shfl_sync(0xffffffffu, o0, src + 1);
        const float b0 = __shfl_sync(0xffffffffu, o1, src), b1 = __shfl_sync(0xffffffffu, o1, src + 1);
        if (lane < 8)
            *reinterpret_cast<uint32_t*>(out + b * DM + h * 16 + 2 * lane) = lane < 4 ? pack_bf16(a0, a1) : pack_bf16(b0, b1);
        if (lane == 0) { g_epoch[cta] = tag + 1; }
    }
}

}

extern "C" void kernel_launch(void* const* d_in, const int* in_sizes, int n_in, void* d_out, int out_size) {
    (void)in_sizes; (void)n_in; (void)out_size;
    const __nv_bfloat16* x  = (const __nv_bfloat16*)d_in[0];
    const __nv_bfloat16* Kc = (const __nv_bfloat16*)d_in[1];
    const __nv_bfloat16* Vc = (const __nv_bfloat16*)d_in[2];
    const __nv_bfloat16* wq = (const __nv_bfloat16*)d_in[3];
    const __nv_bfloat16* wo = (const __nv_bfloat16*)d_in[4];
    const __nv_bfloat16* w1 = (const __nv_bfloat16*)d_in[6];
    const __nv_bfloat16* w2 = (const __nv_bfloat16*)d_in[7];

    static bool attr_set = false;
    if (!attr_set) {
        cudaFuncSetAttribute(fk::fused_decode_kernel, cudaFuncAttributeMaxDynamicSharedMemorySize, fk::SMEM_BYTES);
        attr_set = true;
    }
    fk::fused_decode_kernel<<<fk::N_CTA, fk::NTHREADS, fk::SMEM_BYTES>>>(x, Kc, Vc, wq, wo, w1, w2, (__nv_bfloat16*)d_out);
}
```

```cpp
#include <cuda_runtime.h>
#include <cuda_bf16.h>
#include <stdint.h>

namespace fk {

#define FK_NST 4
#define FK_FIRST 2
#define FK_PRE 1
#define FK_INIT_AT 56
#define FK_WTILE 4
#define FK_WSTEP 10
#define FK_LEAD 0
#define FK_ENDT 16
#define FK_LEAD_END 40

constexpr int NB = 4, NH = 32, SK = 8192, DH = 128, DM = 512, FF = 1376;
constexpr int TK = 128;
constexpr int NT = SK / TK;
constexpr int STAGE_BYTES = TK * DH * 2;
constexpr int NST = FK_NST;
constexpr int NCW = 8;
constexpr int NTHREADS = NCW * 32;
constexpr int N_ATT = NB * NH;
constexpr int N_FFN = 4;
constexpr int FS = FF / N_FFN;
constexpr int N_CTA = N_ATT + N_FFN;
constexpr int NSEQ = 2 * NT;
static_assert(NST % 2 == 0, "K tiles live in the even stages, V tiles in the odd ones");

constexpr int OFF_W   = NST * STAGE_BYTES;
constexpr int OFF_XN  = OFF_W;
constexpr int OFF_X   = OFF_W + 8192;
constexpr int OFF_RED = OFF_W + 12288;
constexpr int OFF_BAR = OFF_W + STAGE_BYTES;
constexpr int OFF_Q   = OFF_BAR + 256;
constexpr int OFF_ML  = OFF_Q + 256;
constexpr int OFF_O   = OFF_ML + 64;
constexpr int SMEM_ATT = OFF_O + 256;
constexpr int FFN_CHUNK = 64 * FS * 2;
constexpr int NBF = (NST >= 6) ? 4 : 2;
constexpr int FFN_XN = NBF * FFN_CHUNK, FFN_H = FFN_XN + 8192, FFN_RED = FFN_H + 5504, FFN_BAR = FFN_RED + 32768;
constexpr int SMEM_FFN = FFN_BAR + 64;
static_assert(FFN_CHUNK == 43 * DM * 2, "chunk geometry");
constexpr int SMEM_BYTES = SMEM_ATT > SMEM_FFN ? SMEM_ATT : SMEM_FFN;

__device__ __align__(256) uint4 g_q_part[NH * NB * 32];
__device__ __align__(256) uint4 g_attn_part[NB * 32 * NH * 8];
__device__ __align__(256) uint4 g_ffn_part[NB * 32 * N_FFN * 8];
__device__ __align__(256) uint32_t g_progress[64];
#define FK_ONE4 1u, 1u, 1u, 1u
#define FK_ONE16 FK_ONE4, FK_ONE4, FK_ONE4, FK_ONE4
#define FK_ONE64 FK_ONE16, FK_ONE16, FK_ONE16, FK_ONE16
__device__ __align__(256) uint32_t g_epoch[N_CTA] = {FK_ONE64, FK_ONE64, FK_ONE4};

__device__ __forceinline__ uint32_t smem_u32(const void* p) { return (uint32_t)__cvta_generic_to_shared(p); }

__device__ __forceinline__ void mbar_init(uint32_t bar, uint32_t cnt) {
    asm volatile("mbarrier.init.shared::cta.b64 [%0], %1;" :: "r"(bar), "r"(cnt) : "memory");
}
__device__ __forceinline__ void mbar_expect_tx(uint32_t bar, uint32_t bytes) {
    asm volatile("mbarrier.arrive.expect_tx.shared::cta.b64 _, [%0], %1;" :: "r"(bar), "r"(bytes) : "memory");
}
__device__ __forceinline__ uint32_t atom_inc_shared(uint32_t addr) {
    uint32_t old;
    asm volatile("atom.relaxed.cta.shared::cta.add.u32 %0, [%1], 1;" : "=r"(old) : "r"(addr) : "memory");
    return old;
}
__device__ __forceinline__ void mbar_wait(uint32_t bar, uint32_t parity) {
    asm volatile(
        "{\n"
        ".reg .pred p;\n"
        "FK_WAIT:\n"
        "mbarrier.try_wait.parity.shared::cta.b64 p, [%0], %1;\n"
        "@p bra FK_DONE;\n"
        "bra FK_WAIT;\n"
        "FK_DONE:\n"
        "}\n" :: "r"(bar), "r"(parity) : "memory");
}
__device__ __forceinline__ void bulk_load(uint32_t dst, const void* src, uint32_t bytes, uint32_t bar, uint64_t pol) {
    asm volatile("cp.async.bulk.shared::cluster.global.mbarrier::complete_tx::bytes.L2::cache_hint [%0], [%1], %2, [%3], %4;"
                 :: "r"(dst), "l"(src), "r"(bytes), "r"(bar), "l"(pol) : "memory");
}
__device__ __forceinline__ uint4 ldg_nc(const void* p) {
    uint4 v;
    asm volatile("ld.global.nc.L1::no_allocate.v4.u32 {%0,%1,%2,%3}, [%4];"
                 : "=r"(v.x), "=r"(v.y), "=r"(v.z), "=r"(v.w) : "l"(p));
    return v;
}
__device__ __forceinline__ void bulk_load_plain(uint32_t dst, const void* src, uint32_t bytes, uint32_t bar) {
    asm volatile("cp.async.bulk.shared::cluster.global.mbarrier::complete_tx::bytes [%0], [%1], %2, [%3];"
                 :: "r"(dst), "l"(src), "r"(bytes), "r"(bar) : "memory");
}
__device__ __forceinline__ uint32_t ldg_nc32(const void* p) {
    uint32_t v;
    asm volatile("ld.global.nc.L1::no_allocate.u32 %0, [%1];" : "=r"(v) : "l"(p));
    return v;
}
__device__ __forceinline__ uint32_t lds32(uint32_t addr) {
    uint32_t v;
    asm volatile("ld.volatile.shared.u32 %0, [%1];" : "=r"(v) : "r"(addr) : "memory");
    return v;
}
__device__ __forceinline__ uint32_t pin(uint32_t v) {
    uint32_t r;
    asm volatile("mov.b32 %0, %1;" : "=r"(r) : "r"(v));
    return r;
}
__device__ __forceinline__ uint32_t ld_relaxed32(const uint32_t* p) {
    uint32_t v;
    asm volatile("ld.relaxed.gpu.global.u32 %0, [%1];" : "=r"(v) : "l"(p) : "memory");
    return v;
}
__device__ __forceinline__ bool mbar_test(uint32_t bar, uint32_t parity) {
    uint32_t ok;
    asm volatile("{\n.reg .pred p;\nmbarrier.test_wait.parity.shared::cta.b64 p, [%1], %2;\nselp.u32 %0, 1, 0, p;\n}\n"
                 : "=r"(ok) : "r"(bar), "r"(parity) : "memory");
    return ok != 0;
}
__device__ __forceinline__ uint4 ld_relaxed(const uint4* p) {
    uint4 v;
    asm volatile("ld.relaxed.gpu.global.v4.u32 {%0,%1,%2,%3}, [%4];"
                 : "=r"(v.x), "=r"(v.y), "=r"(v.z), "=r"(v.w) : "l"(p) : "memory");
    return v;
}
__device__ __forceinline__ void st_relaxed(uint4* p, uint4 v) {
    asm volatile("st.relaxed.gpu.global.v4.u32 [%0], {%1,%2,%3,%4};"
                 :: "l"(p), "r"(v.x), "r"(v.y), "r"(v.z), "r"(v.w) : "memory");
}
__device__ __forceinline__ void ldsm_x4(uint32_t (&r)[4], uint32_t addr) {
    asm volatile("ldmatrix.sync.aligned.m8n8.x4.shared.b16 {%0,%1,%2,%3}, [%4];"
                 : "=r"(r[0]), "=r"(r[1]), "=r"(r[2]), "=r"(r[3]) : "r"(addr) : "memory");
}
__device__ __forceinline__ void ldsm_x4_t(uint32_t (&r)[4], uint32_t addr) {
    asm volatile("ldmatrix.sync.aligned.m8n8.x4.trans.shared.b16 {%0,%1,%2,%3}, [%4];"
                 : "=r"(r[0]), "=r"(r[1]), "=r"(r[2]), "=r"(r[3]) : "r"(addr) : "memory");
}
__device__ __forceinline__ void mma_bf16(float (&c)[4], const uint32_t (&a)[4], uint32_t b0, uint32_t b1) {
    asm volatile("mma.sync.aligned.m16n8k16.row.col.f32.bf16.bf16.f32 {%0,%1,%2,%3}, {%4,%5,%6,%7}, {%8,%9}, {%0,%1,%2,%3};"
                 : "+f"(c[0]), "+f"(c[1]), "+f"(c[2]), "+f"(c[3])
                 : "r"(a[0]), "r"(a[1]), "r"(a[2]), "r"(a[3]), "r"(b0), "r"(b1));
}
__device__ __forceinline__ float ex2(float x) {
    float r;
    asm("ex2.approx.ftz.f32 %0, %1;" : "=f"(r) : "f"(x));
    return r;
}
__device__ __forceinline__ uint32_t pack_bf16(float lo, float hi) {
    uint32_t r;
    asm("cvt.rn.bf16x2.f32 %0, %1, %2;" : "=r"(r) : "f"(hi), "f"(lo));
    return r;
}
__device__ __forceinline__ float bf_lo(uint32_t w) { return __uint_as_float(w << 16); }
__device__ __forceinline__ float bf_hi(uint32_t w) { return __uint_as_float(w & 0xffff0000u); }
__device__ __forceinline__ float bf16r(float x) { return __bfloat162float(__float2bfloat16_rn(x)); }
__device__ __forceinline__ float silu_f(float x) { return x / (1.0f + __expf(-x)); }

__device__ __forceinline__ void warp_layernorm(const uint4 a, const uint4 b, float (&xn)[16]) {
    float v[16];
    v[0] = bf_lo(a.x); v[1] = bf_hi(a.x); v[2] = bf_lo(a.y); v[3] = bf_hi(a.y);
    v[4] = bf_lo(a.z); v[5] = bf_hi(a.z); v[6] = bf_lo(a.w); v[7] = bf_hi(a.w);
    v[8] = bf_lo(b.x); v[9] = bf_hi(b.x); v[10] = bf_lo(b.y); v[11] = bf_hi(b.y);
    v[12] = bf_lo(b.z); v[13] = bf_hi(b.z); v[14] = bf_lo(b.w); v[15] = bf_hi(b.w);
    float s = 0.f;
#pragma unroll
    for (int i = 0; i < 16; i++) s += v[i];
#pragma unroll
    for (int o = 16; o; o >>= 1) s += __shfl_xor_sync(0xffffffffu, s, o);
    const float mean = s * (1.0f / DM);
    float ss = 0.f;
#pragma unroll
    for (int i = 0; i < 16; i++) { const float d = v[i] - mean; ss = fmaf(d, d, ss); }
#pragma unroll
    for (int o = 16; o; o >>= 1) ss += __shfl_xor_sync(0xffffffffu, ss, o);
    const float m_bf = bf16r(mean);
    const float den = bf16r(sqrtf(bf16r(bf16r(ss * (1.0f / DM)) + 1e-5f)));
#pragma unroll
    for (int i = 0; i < 16; i++) xn[i] = bf16r(__fdiv_rn(bf16r(v[i] - m_bf), den));
}

__device__ __forceinline__ bool ll_valid(const uint4& v, uint32_t tag) { return v.y == tag && v.w == tag; }

__device__ __forceinline__ void ffn_cta(uint8_t* smem, int f, uint32_t tag,
                                        const __nv_bfloat16* __restrict__ x,
                                        const __nv_bfloat16* __restrict__ w1,
                                        const __nv_bfloat16* __restrict__ w2) {
    const int tid = threadIdx.x, warp = tid >> 5, lane = tid & 31;
    const uint32_t sbase = smem_u32(smem), bar = sbase + FFN_BAR;
    float* xnT = reinterpret_cast<float*>(smem + FFN_XN);
    float* hT  = reinterpret_cast<float*>(smem + FFN_H);
    float* red = reinterpret_cast<float*>(smem + FFN_RED);
    if (tid == 0) {
#pragma unroll
        for (int s = 0; s < NBF; s++) mbar_init(bar + s * 8, 1);
    }
    __syncthreads();
    auto issue = [&](int c) {
        const int s = c % NBF;
        if (tid == 0) mbar_expect_tx(bar + s * 8, FFN_CHUNK);
        if (c < 8) {
            __syncthreads();
            if (tid < 64) bulk_load_plain(sbase + s * FFN_CHUNK + tid * (FS * 2), w1 + (size_t)(c * 64 + tid) * FF + f * FS, FS * 2, bar + s * 8);
        } else if (tid == 0) {
            bulk_load_plain(sbase + s * FFN_CHUNK, w2 + (size_t)(f * FS + (c - 8) * 43) * DM, FFN_CHUNK, bar + s * 8);
        }
    };
    for (int c = 0; c < NBF; c++) issue(c);
    if (warp < NB) {
        float xn[16];
        const uint4 xa = ldg_nc(x + warp * DM + lane * 16), xb = ldg_nc(x + warp * DM + lane * 16 + 8);
        warp_layernorm(xa, xb, xn);
#pragma unroll
        for (int i = 0; i < 16; i++) xnT[(lane * 16 + i) * 4 + warp] = xn[i];
    }
    __syncthreads();
    float acc[4][8];
#pragma unroll
    for (int b = 0; b < 4; b++)
#pragma unroll
        for (int c = 0; c < 8; c++) acc[b][c] = 0.f;
#pragma unroll 1
    for (int c = 0; c < 16; c++) {
        const int s = c % NBF;
        mbar_wait(bar + s * 8, (c / NBF) & 1);
        const bool st1 = c < 8;
        const int cg = st1 ? tid % 43 : (tid & 63), r0 = st1 ? tid / 43 : (tid >> 6);
        const int rstep = st1 ? 5 : 4, nrows = st1 ? 64 : 43, rbytes = st1 ? FS * 2 : DM * 2;
        const float* vec = st1 ? xnT + c * 64 * 4 : hT + (c - 8) * 43 * 4;
        const uint8_t* wb = smem + s * FFN_CHUNK + cg * 16;
        if (!st1 || tid < 43 * 5) {
#pragma unroll 2
            for (int k = r0; k < nrows; k += rstep) {
                const uint4 w = *reinterpret_cast<const uint4*>(wb + k * rbytes);
                const float4 xv = *reinterpret_cast<const float4*>(vec + k * 4);
                const float wf[8] = {bf_lo(w.x), bf_hi(w.x), bf_lo(w.y), bf_hi(w.y), bf_lo(w.z), bf_hi(w.z), bf_lo(w.w), bf_hi(w.w)};
#pragma unroll
                for (int j = 0; j < 8; j++) {
                    acc[0][j] = fmaf(xv.x, wf[j], acc[0][j]);
                    acc[1][j] = fmaf(xv.y, wf[j], acc[1][j]);
                    acc[2][j] = fmaf(xv.z, wf[j], acc[2][j]);
                    acc[3][j] = fmaf(xv.w, wf[j], acc[3][j]);
                }
            }
        }
        __syncthreads();
        if (c + NBF < 16) issue(c + NBF);
        if (c == 7) {
            if (tid < 43 * 5) {
#pragma unroll
                for (int b = 0; b < 4; b++)
#pragma unroll
                    for (int j = 0; j < 8; j++) red[(r0 * 4 + b) * FS + cg * 8 + j] = acc[b][j];
            }
#pragma unroll
            for (int b = 0; b < 4; b++)
#pragma unroll
                for (int j = 0; j < 8; j++) acc[b][j] = 0.f;
            __syncthreads();
            for (int i = tid; i < 4 * FS; i += NTHREADS) {
                const int b = i / FS, cc = i % FS;
                float sum = 0.f;
#pragma unroll
                for (int ks = 0; ks < 5; ks++) sum += red[(ks * 4 + b) * FS + cc];
                hT[cc * 4 + b] = bf16r(silu_f(bf16r(sum)));
            }
            __syncthreads();
        }
    }
    {
        const int cg = tid & 63, fs = tid >> 6;
#pragma unroll
        for (int b = 0; b < 4; b++)
#pragma unroll
            for (int j = 0; j < 8; j++) red[(fs * 4 + b) * DM + cg * 8 + j] = acc[b][j];
    }
    __syncthreads();
    for (int i = tid; i < NB * 256; i += NTHREADS) {
        const int b = i >> 8, j = (i >> 3) & 31, p = i & 7;
        float s0 = 0.f, s1 = 0.f;
#pragma unroll
        for (int fs = 0; fs < 4; fs++) { s0 += red[(fs * 4 + b) * DM + 16 * j + p]; s1 += red[(fs * 4 + b) * DM + 16 * j + 8 + p]; }
        st_relaxed(&g_ffn_part[((b * 32 + j) * N_FFN + f) * 8 + p],
                   make_uint4(__float_as_uint(s0), tag, __float_as_uint(s1), tag));
    }
}

__global__ void __launch_bounds__(NTHREADS, 1)
fused_decode_kernel(const __nv_bfloat16* __restrict__ x, const __nv_bfloat16* __restrict__ Kc,
                    const __nv_bfloat16* __restrict__ Vc, const __nv_bfloat16* __restrict__ wq,
                    const __nv_bfloat16* __restrict__ wo, const __nv_bfloat16* __restrict__ w1,
                    const __nv_bfloat16* __restrict__ w2, __nv_bfloat16* __restrict__ out) {
    extern __shared__ __align__(1024) uint8_t smem[];
    const int cta = blockIdx.x;
    const int tid = threadIdx.x, warp = tid >> 5, lane = tid & 31;
    if (cta >= N_ATT) {
        const uint32_t tag = ld_relaxed32(&g_epoch[cta]);
        ffn_cta(smem, cta - N_ATT, tag, x, w1, w2);
        if (tid == 0) { g_epoch[cta] = tag + 1; }
        return;
    }

    const int b = cta & 3, h = cta >> 2;
    const int bh = b * NH + h;
    const uint32_t sbase = pin(smem_u32(smem));
    const uint32_t bar_full = sbase + OFF_BAR;
    const uint32_t cnt_rel = bar_full + NST * 8;
    const char* kp = reinterpret_cast<const char*>(Kc) + (size_t)bh * SK * DH * 2;
    const char* vp = reinterpret_cast<const char*>(Vc) + (size_t)bh * SK * DH * 2;
    const char* wop = reinterpret_cast<const char*>(wo) + (size_t)h * DH * DM * 2;
    uint64_t pol;
    asm volatile("createpolicy.fractional.L2::evict_first.b64 %0, 1.0;" : "=l"(pol));
    auto issue_kv = [&](const char* src, int s) {
        const uint32_t bar = bar_full + s * 8;
        mbar_expect_tx(bar, STAGE_BYTES);
        bulk_load(sbase + s * STAGE_BYTES, src, STAGE_BYTES, bar, pol);
    };
    auto issue_first = [&](int n) { issue_kv(((n & 1) ? vp : kp) + (size_t)(n >> 1) * STAGE_BYTES, n); };
    const uint32_t bar_w = bar_full + 216, cnt_w = bar_full + 224;
    auto issue_w = [&](int q) {
        mbar_expect_tx(bar_w, STAGE_BYTES);
        bulk_load_plain(sbase + OFF_W, wop + (size_t)q * STAGE_BYTES, STAGE_BYTES, bar_w);
    };

    const int g = lane >> 2, t = lane & 3;
    float* xn_s  = reinterpret_cast<float*>(smem + OFF_XN);
    float* red_s = reinterpret_cast<float*>(smem + OFF_RED);
    __nv_bfloat16* q_s = reinterpret_cast<__nv_bfloat16*>(smem + OFF_Q);
    float* ml_s = reinterpret_cast<float*>(smem + OFF_ML);
    __nv_bfloat16* o_s = reinterpret_cast<__nv_bfloat16*>(smem + OFF_O);

    uint4* const q_out = &g_q_part[(h * NB + (lane >> 3)) * 32 + b * 8 + (lane & 7)];
    uint4* const a_out = &g_attn_part[((b * 32 + warp * 4 + t) * NH + h) * 8 + g];

    volatile uint32_t* q_flag = reinterpret_cast<volatile uint32_t*>(smem + OFF_BAR + 192);
    const uint32_t bar_x = bar_full + 200;
    if (tid == 0) {
        mbar_init(bar_full, 1);
        issue_first(0);
        mbar_init(bar_x, 1);
        mbar_expect_tx(bar_x, NB * DM * 2);
        bulk_load_plain(sbase + OFF_X, x, NB * DM * 2, bar_x);
#pragma unroll
        for (int s = 1; s < NST; s++) mbar_init(bar_full + s * 8, 1);
        mbar_init(bar_w, 1);
#pragma unroll
        for (int s = 0; s < NST; s++) *reinterpret_cast<volatile uint32_t*>(smem + OFF_BAR + NST * 8 + s * 4) = 0;
        *reinterpret_cast<volatile uint32_t*>(smem + OFF_BAR + 224) = 0;
        *q_flag = 0;
#pragma unroll 1
        for (int s = 1; s < FK_PRE; s++) issue_first(s);
    }
    uint32_t qf[8][2];
    uint32_t tag;
    {
        uint32_t w[32];
        const __nv_bfloat16* wp = wq + (size_t)(warp * 64 + (lane >> 4) * 32) * (NH * DH) + h * DH + b * 32 + (lane & 15) * 2;
#pragma unroll
        for (int i = 0; i < 32; i++) w[i] = ldg_nc32(wp + (size_t)i * (NH * DH));
        tag = ld_relaxed32(&g_epoch[cta]);
        if (tid == 0) {
#pragma unroll 1
            for (int s = FK_PRE; s < FK_FIRST; s++) issue_first(s);
            asm volatile("prefetch.global.L2 [%0];" :: "l"(wop));
        }
        if (warp == 0) st_relaxed(q_out, make_uint4(0, 0, 0, 0));
        if (FK_INIT_AT < 0) st_relaxed(a_out, make_uint4(0, 0, 0, 0));
        __syncthreads();
        if (warp < 4) {
            float xn[16];
            mbar_wait(bar_x, 0);
            const uint4 xa = *reinterpret_cast<const uint4*>(smem + OFF_X + warp * DM * 2 + lane * 32);
            const uint4 xb = *reinterpret_cast<const uint4*>(smem + OFF_X + warp * DM * 2 + lane * 32 + 16);
            warp_layernorm(xa, xb, xn);
#pragma unroll
            for (int i = 0; i < 16; i += 4)
                *reinterpret_cast<float4*>(xn_s + warp * DM + lane * 16 + i) = make_float4(xn[i], xn[i + 1], xn[i + 2], xn[i + 3]);
        }
        __syncthreads();
        float acc[4][2];
#pragma unroll
        for (int bb = 0; bb < 4; bb++) acc[bb][0] = acc[bb][1] = 0.f;
        const float* xp = xn_s + warp * 64 + (lane >> 4) * 32;
#pragma unroll
        for (int i4 = 0; i4 < 8; i4++) {
#pragma unroll
            for (int bb = 0; bb < 4; bb++) {
                const float4 xv = *reinterpret_cast<const float4*>(xp + bb * DM + i4 * 4);
                const float xs[4] = {xv.x, xv.y, xv.z, xv.w};
#pragma unroll
                for (int u = 0; u < 4; u++) {
                    acc[bb][0] = fmaf(xs[u], bf_lo(w[i4 * 4 + u]), acc[bb][0]);
                    acc[bb][1] = fmaf(xs[u], bf_hi(w[i4 * 4 + u]), acc[bb][1]);
                }
            }
        }
        const bool up = lane >= 16;
        float k0 = up ? acc[2][0] : acc[0][0], k1 = up ? acc[2][1] : acc[0][1];
        float k2 = up ? acc[3][0] : acc[1][0], k3 = up ? acc[3][1] : acc[1][1];
        k0 += __shfl_xor_sync(0xffffffffu, up ? acc[0][0] : acc[2][0], 16);
        k1 += __shfl_xor_sync(0xffffffffu, up ? acc[0][1] : acc[2][1], 16);
        k2 += __shfl_xor_sync(0xffffffffu, up ? acc[1][0] : acc[3][0], 16);
        k3 += __shfl_xor_sync(0xffffffffu, up ? acc[1][1] : acc[3][1], 16);
        float* rp = red_s + warp * 128 + (up ? 64 : 0) + (lane & 15) * 2;
        *reinterpret_cast<float2*>(rp)      = make_float2(k0, k1);
        *reinterpret_cast<float2*>(rp + 32) = make_float2(k2, k3);
        __syncthreads();
        if (warp == 0) {
            float4 s = make_float4(0.f, 0.f, 0.f, 0.f);
#pragma unroll
            for (int w8 = 0; w8 < NCW; w8++) {
                const float4 v = *reinterpret_cast<const float4*>(red_s + w8 * 128 + lane * 4);
                s.x += v.x; s.y += v.y; s.z += v.z; s.w += v.w;
            }
            st_relaxed(q_out, make_uint4(pack_bf16(s.x, s.y), tag, pack_bf16(s.z, s.w), tag));
            const uint4* p = &g_q_part[(h * NB + b) * 32 + lane];
            uint4 v = ld_relaxed(p);
            for (int spin = 0; !ll_valid(v, tag) && spin < (1 << 20); spin++) v = ld_relaxed(p);
            *reinterpret_cast<uint2*>(q_s + lane * 4) = make_uint2(v.x, v.z);
            if (lane == 0) *q_flag = 1;
        }
        if (tid == NTHREADS - 32) {
            int next = FK_FIRST, watch = 0;
            while (next < NST) {
                if (mbar_test(bar_full + watch * 8, 0)) { issue_first(next); next++; watch++; }
                else if (*q_flag) break;
            }
#pragma unroll 1
            for (; next < NST; next++) issue_first(next);
        }
        __syncthreads();
#pragma unroll
        for (int j = 0; j < 8; j++) {
            const int c = (j ^ g) & 7;
            qf[j][0] = *reinterpret_cast<const uint32_t*>(q_s + c * 8 + 2 * t);
            qf[j][1] = *reinterpret_cast<const uint32_t*>(q_s + 64 + c * 8 + 2 * t);
        }
    }

    constexpr float RSQRT_DH = 0.08838834764831845f, LOG2E = 1.4426950408889634f;
    const int li = lane & 7, lm = lane >> 3;
    const uint32_t k_base = pin(sbase + (uint32_t)((warp * 16 + li + 8 * (lm & 1)) * 256 + (lm >> 1) * 128 + li * 16));
    const uint32_t v_base = pin(sbase + (uint32_t)((warp * 16 + li + 8 * (lm >> 1)) * 256 + (lm & 1) * 128 + li * 16));
    const bool diag = (t == (g >> 1));
    uint32_t msk[8];
#pragma unroll
    for (int j = 0; j < 8; j++) msk[j] = pin((j == (g ^ (2 * t)) ? 0x0000ffffu : 0u) | (j == (g ^ (2 * t) ^ 1) ? 0xffff0000u : 0u));
    const uint32_t ones[4] = {0x3f803f80u, 0x3f803f80u, 0x3f803f80u, 0x3f803f80u};

    float acc0[4] = {0.f, 0.f, 0.f, 0.f}, acc1[4] = {0.f, 0.f, 0.f, 0.f}, lacc[4] = {0.f, 0.f, 0.f, 0.f};
    float m_raw = -INFINITY;
    float m_run = -INFINITY, mc = 0.f;
    float fin_scale = 0.f;
    int st = 0; uint32_t ph = 0;
    int seq = NST;
    uint32_t wa[8][4][4];
    float g0 = 0.f, g1 = 0.f;
    uint4 gv = make_uint4(0, 0, 0, 0);
    const int cp = lane & 7, q4 = lane >> 3;
    const float x0 = __bfloat162float(reinterpret_cast<const __nv_bfloat16*>(smem + OFF_X)[b * DM + h * 16 + cp]);
    const float x1 = __bfloat162float(reinterpret_cast<const __nv_bfloat16*>(smem + OFF_X)[b * DM + h * 16 + 8 + cp]);
    const uint32_t prog_base = (tag - 1) * (uint32_t)(N_ATT * NT);
    const uint32_t prog_s = bar_full + 208;
    uint32_t prog_v = prog_base;
    if (tid == 0) *reinterpret_cast<volatile uint32_t*>(smem + OFF_BAR + 208) = prog_base;
    __syncthreads();
    auto pace = [&](uint32_t pv, uint32_t lim) {
        for (int spin = 0; (int)(pv - lim) < 0 && spin < 4096; spin++) pv = ld_relaxed32(&g_progress[0]);
    };

#pragma unroll 1
    for (int it = 0; it < NT; it++) {
#pragma unroll
        for (int q = 0; q <= 4; q++) {
            if (it == FK_WTILE + q * FK_WSTEP) {
                if (q == 0) {
                    if (tid == 0) {
                        asm volatile("fence.proxy.async.shared::cta;" ::: "memory");
                        issue_w(0);
                    }
                } else {
                    mbar_wait(bar_w, (q - 1) & 1);
                    const uint32_t wb = sbase + OFF_W + (li + 8 * (lane >> 4)) * 1024 + warp * 128 + (lm & 1) * 16;
#pragma unroll
                    for (int j = 0; j < 4; j++) {
                        ldsm_x4_t(wa[2 * q - 2][j], wb + j * 32);
                        ldsm_x4_t(wa[2 * q - 1][j], wb + 16384 + j * 32);
                    }
                    if (q < 4 && lane == 0) {
                        const uint32_t rel = atom_inc_shared(cnt_w);
                        if ((rel & (NCW - 1)) == NCW - 1) issue_w(q);
                    }
                }
                __syncwarp();
            }
        }
        if (it == FK_INIT_AT) st_relaxed(a_out, make_uint4(0, 0, 0, 0));
        if (it == NT - 12 && warp == 0) {
            gv = ld_relaxed(&g_ffn_part[((b * 32 + h) * N_FFN + q4) * 8 + cp]);
        }
        if (it == NT - 2 && warp == 0) {
            const uint4* p = &g_ffn_part[((b * 32 + h) * N_FFN + q4) * 8 + cp];
            uint4 v = gv;
            for (int spin = 0; !ll_valid(v, tag) && spin < (1 << 20); spin++) { __nanosleep(64); v = ld_relaxed(p); }
            __syncwarp();
            g0 = __uint_as_float(v.x); g1 = __uint_as_float(v.z);
            g0 += __shfl_xor_sync(0xffffffffu, g0, 8);  g1 += __shfl_xor_sync(0xffffffffu, g1, 8);
            g0 += __shfl_xor_sync(0xffffffffu, g0, 16); g1 += __shfl_xor_sync(0xffffffffu, g1, 16);
            g0 = bf16r(silu_f(bf16r(g0))); g1 = bf16r(silu_f(bf16r(g1)));
        }
        if (tid == 0) {
            *reinterpret_cast<volatile uint32_t*>(smem + OFF_BAR + 208) = prog_v;
            prog_v = ld_relaxed32(&g_progress[0]);
        }
        const bool endgame = it >= NT - FK_ENDT;
        const char* k_next = kp + (size_t)(it + NST / 2) * STAGE_BYTES;
        const char* v_next = vp + (size_t)(it + NST / 2) * STAGE_BYTES;
        mbar_wait(bar_full + st * 8, ph);
        float c0[4] = {0.f, 0.f, 0.f, 0.f}, c1[4] = {0.f, 0.f, 0.f, 0.f};
        uint32_t relK = 0, pvK = 0;
        const uint32_t kb = k_base + st * STAGE_BYTES;
        {
#pragma unroll
            for (int j = 0; j < 8; j++) {
                uint32_t a[4];
                ldsm_x4(a, kb ^ (j << 4));
                mma_bf16((j & 1) ? c1 : c0, a, qf[j][0], qf[j][1]);
            }
            if (!endgame && seq < NSEQ && lane == 0) {
                relK = atom_inc_shared(cnt_rel + st * 4);
                pvK = lds32(prog_s);
            }
        }
        const float u0 = (g & 1) ? (c0[1] + c1[1]) : (c0[0] + c1[0]);
        const float u1 = (g & 1) ? (c0[3] + c1[3]) : (c0[2] + c1[2]);
        int key = __float_as_int(diag ? fmaxf(u0, u1) : -INFINITY);
        key ^= (key >> 31) & 0x7fffffff;
        key = __reduce_max_sync(0xffffffffu, key);
        const uint32_t r1 = pack_bf16(u0, u1);
        const uint32_t r2 = pack_bf16(bf_lo(r1) * RSQRT_DH, bf_hi(r1) * RSQRT_DH);
        const float s0 = diag ? bf_lo(r2) : -INFINITY, s1 = diag ? bf_hi(r2) : -INFINITY;
        key ^= (key >> 31) & 0x7fffffff;
        const float tmax = __int_as_float(key);
        if (tmax > m_raw) {
            m_raw = tmax;
            const float m_new = bf16r(bf16r(tmax) * RSQRT_DH);
            const float sc = ex2((m_run - m_new) * LOG2E);
#pragma unroll
            for (int i = 0; i < 4; i++) { acc0[i] *= sc; acc1[i] *= sc; }
            lacc[0] *= sc;
            m_run = m_new;
            mc = -m_new * LOG2E;
        }
        const uint32_t pk = pack_bf16(ex2(fmaf(s0, LOG2E, mc)), ex2(fmaf(s1, LOG2E, mc)));
        const uint32_t xx = __shfl_sync(0xffffffffu, pk, 9 * t), yy = __shfl_sync(0xffffffffu, pk, 9 * t + 4);
        const uint32_t pp0 = __byte_perm(xx, yy, 0x5410), pp1 = __byte_perm(xx, yy, 0x7632);
        if ((relK & (NCW - 1)) == NCW - 1) {
            pace(pvK, prog_base + (uint32_t)(it * N_ATT - (FK_LEAD)));
            issue_kv(k_next, st);
        }
        __syncwarp();
        const int stK = st;
        seq++;
        if (++st == NST) { st = 0; ph ^= 1; }
        mma_bf16(lacc, ones, pp0, pp1);
        if (it == NT - 1) {
            if (lane == 0) { ml_s[warp] = m_run; ml_s[8 + warp] = lacc[0]; }
            __syncthreads();
            const float4 ma = *reinterpret_cast<const float4*>(ml_s), mb = *reinterpret_cast<const float4*>(ml_s + 4);
            const float4 la = *reinterpret_cast<const float4*>(ml_s + 8), lb = *reinterpret_cast<const float4*>(ml_s + 12);
            const float M = fmaxf(fmaxf(fmaxf(ma.x, ma.y), fmaxf(ma.z, ma.w)), fmaxf(fmaxf(mb.x, mb.y), fmaxf(mb.z, mb.w)));
            const float L = (ex2((ma.x - M) * LOG2E) * la.x + ex2((ma.y - M) * LOG2E) * la.y) + (ex2((ma.z - M) * LOG2E) * la.z + ex2((ma.w - M) * LOG2E) * la.w)
                          + (ex2((mb.x - M) * LOG2E) * lb.x + ex2((mb.y - M) * LOG2E) * lb.y) + (ex2((mb.z - M) * LOG2E) * lb.z + ex2((mb.w - M) * LOG2E) * lb.w);
            fin_scale = __fdividef(ex2((m_run - M) * LOG2E), L);
        }
        mbar_wait(bar_full + st * 8, ph);
        const uint32_t vb = v_base + st * STAGE_BYTES;
        {
            uint32_t relV = 0, pvV = 0;
#pragma unroll
            for (int j = 0; j < 8; j++) {
                uint32_t a[4];
                ldsm_x4_t(a, vb ^ (j << 4));
                mma_bf16((j & 1) ? acc1 : acc0, a, pp0 & msk[j], pp1 & msk[j]);
            }
            if (seq - (endgame ? 1 : 0) < NSEQ && lane == 0) {
                relV = atom_inc_shared(cnt_rel + st * 4);
                pvV = lds32(prog_s);
            }
            if (tid == NTHREADS - 32) asm volatile("red.relaxed.gpu.global.add.u32 [%0], 1;" :: "l"(&g_progress[0]) : "memory");
            if ((relV & (NCW - 1)) == NCW - 1) {
                if (endgame) {
                    pace(pvV, prog_base + (uint32_t)((it + 1) * N_ATT - (FK_LEAD_END)));
                    issue_kv(k_next, stK);
                }
                if (seq < NSEQ) issue_kv(v_next, st);
            }
        }
        __syncwarp();
        seq++;
        if (++st == NST) { st = 0; ph ^= 1; }
    }

    {
        float* o = red_s + warp * 128;
        o[16 * t + g]          = (acc0[0] + acc1[0]) * fin_scale;
        o[16 * t + 8 + g]      = (acc0[1] + acc1[1]) * fin_scale;
        o[64 + 16 * t + g]     = (acc0[2] + acc1[2]) * fin_scale;
        o[64 + 16 * t + 8 + g] = (acc0[3] + acc1[3]) * fin_scale;
    }
    __syncthreads();
    if (tid < DH) {
        float v[8];
#pragma unroll
        for (int w = 0; w < 8; w++) v[w] = red_s[w * 128 + tid];
        const float o = ((v[0] + v[1]) + (v[2] + v[3])) + ((v[4] + v[5]) + (v[6] + v[7]));
        o_s[((tid >> 1) & 3) * 32 + (tid >> 4) * 4 + ((tid >> 3) & 1) * 2 + (tid & 1)] = __float2bfloat16_rn(o);
    }
    __syncthreads();
    {
        float d[4][4];
#pragma unroll
        for (int j = 0; j < 4; j++) { d[j][0] = d[j][1] = d[j][2] = d[j][3] = 0.f; }
        uint4 ov[4];
#pragma unroll
        for (int i = 0; i < 4; i++) ov[i] = *reinterpret_cast<const uint4*>(o_s + t * 32 + i * 8);
#pragma unroll
        for (int i = 0; i < 4; i++) {
#pragma unroll
            for (int j = 0; j < 4; j++) mma_bf16(d[j], wa[2 * i][j], ov[i].x, ov[i].y);
#pragma unroll
            for (int j = 0; j < 4; j++) mma_bf16(d[j], wa[2 * i + 1][j], ov[i].z, ov[i].w);
        }
        float r0 = d[0][0], r1 = d[0][2];
        if (t == 1) { r0 = d[1][0]; r1 = d[1][2]; }
        if (t == 2) { r0 = d[2][0]; r1 = d[2][2]; }
        if (t == 3) { r0 = d[3][0]; r1 = d[3][2]; }
        st_relaxed(a_out, make_uint4(__float_as_uint(r0), tag, __float_as_uint(r1), tag));
    }
    if (warp == 0) {
        const uint4* p = &g_attn_part[((b * 32 + h) * NH + q4 * 8) * 8 + cp];
        uint4 v[8];
#pragma unroll
        for (int i = 0; i < 8; i++) v[i] = ld_relaxed(p + i * 8);
        for (int spin = 0; spin < (1 << 20); spin++) {
            bool ok = true;
#pragma unroll
            for (int i = 0; i < 8; i++) {
                if (!ll_valid(v[i], tag)) { v[i] = ld_relaxed(p + i * 8); ok = false; }
            }
            if (ok) break;
        }
        __syncwarp();
        float s0 = ((__uint_as_float(v[0].x) + __uint_as_float(v[1].x)) + (__uint_as_float(v[2].x) + __uint_as_float(v[3].x)))
                 + ((__uint_as_float(v[4].x) + __uint_as_float(v[5].x)) + (__uint_as_float(v[6].x) + __uint_as_float(v[7].x)));
        float s1 = ((__uint_as_float(v[0].z) + __uint_as_float(v[1].z)) + (__uint_as_float(v[2].z) + __uint_as_float(v[3].z)))
                 + ((__uint_as_float(v[4].z) + __uint_as_float(v[5].z)) + (__uint_as_float(v[6].z) + __uint_as_float(v[7].z)));
        s0 += __shfl_xor_sync(0xffffffffu, s0, 8);  s1 += __shfl_xor_sync(0xffffffffu, s1, 8);
        s0 += __shfl_xor_sync(0xffffffffu, s0, 16); s1 += __shfl_xor_sync(0xffffffffu, s1, 16);
        const float o0 = x0 + bf16r(bf16r(s0) * g0), o1 = x1 + bf16r(bf16r(s1) * g1);
        const int src = (2 * lane) & 7;
        const float a0 = __shfl_sync(0xffffffffu, o0, src), a1 = __shfl_sync(0xffffffffu, o0, src + 1);
        const float b0 = __shfl_sync(0xffffffffu, o1, src), b1 = __shfl_sync(0xffffffffu, o1, src + 1);
        if (lane < 8)
            *reinterpret_cast<uint32_t*>(out + b * DM + h * 16 + 2 * lane) = lane < 4 ? pack_bf16(a0, a1) : pack_bf16(b0, b1);
        if (lane == 0) { g_epoch[cta] = tag + 1; }
    }
}

}

extern "C" void kernel_launch(void* const* d_in, const int* in_sizes, int n_in, void* d_out, int out_size) {
    (void)in_sizes; (void)n_in; (void)out_size;
    const __nv_bfloat16* x  = (const __nv_bfloat16*)d_in[0];
    const __nv_bfloat16* Kc = (const __nv_bfloat16*)d_in[1];
    const __nv_bfloat16* Vc = (const __nv_bfloat16*)d_in[2];
    const __nv_bfloat16* wq = (const __nv_bfloat16*)d_in[3];
    const __nv_bfloat16* wo = (const __nv_bfloat16*)d_in[4];
    const __nv_bfloat16* w1 = (const __nv_bfloat16*)d_in[6];
    const __nv_bfloat16* w2 = (const __nv_bfloat16*)d_in[7];

    static bool attr_set = false;
    if (!attr_set) {
        cudaFuncSetAttribute(fk::fused_decode_kernel, cudaFuncAttributeMaxDynamicSharedMemorySize, fk::SMEM_BYTES);
        attr_set = true;
    }
    fk::fused_decode_kernel<<<fk::N_CTA, fk::NTHREADS, fk::SMEM_BYTES>>>(x, Kc, Vc, wq, wo, w1, w2, (__nv_bfloat16*)d_out);
}
```

```cpp
#include <cuda_runtime.h>
#include <cuda_bf16.h>
#include <stdint.h>

namespace fk {

#define FK_NST 4
#define FK_FIRST 2
#define FK_PRE 1
#define FK_INIT_AT 56
#define FK_DRY 1
#define FK_WTILE 4
#define FK_WSTEP 10
#define FK_LEAD 0
#define FK_ENDT 16
#define FK_LEAD_END 48

constexpr int NB = 4, NH = 32, SK = 8192, DH = 128, DM = 512, FF = 1376;
constexpr int TK = 128;
constexpr int NT = SK / TK;
constexpr int STAGE_BYTES = TK * DH * 2;
constexpr int NST = FK_NST;
constexpr int NCW = 8;
constexpr int NTHREADS = NCW * 32;
constexpr int N_ATT = NB * NH;
constexpr int N_FFN = 4;
constexpr int FS = FF / N_FFN;
constexpr int N_CTA = N_ATT + N_FFN;
constexpr int NSEQ = 2 * NT;
static_assert(NST % 2 == 0, "K tiles live in the even stages, V tiles in the odd ones");

constexpr int OFF_W   = NST * STAGE_BYTES;
constexpr int OFF_XN  = OFF_W;
constexpr int OFF_X   = OFF_W + 8192;
constexpr int OFF_RED = OFF_W + 12288;
constexpr int OFF_BAR = OFF_W + STAGE_BYTES;
constexpr int OFF_Q   = OFF_BAR + 256;
constexpr int OFF_ML  = OFF_Q + 256;
constexpr int OFF_O   = OFF_ML + 64;
constexpr int SMEM_ATT = OFF_O + 256;
constexpr int FFN_CHUNK = 64 * FS * 2;
constexpr int NBF = (NST >= 6) ? 4 : 2;
constexpr int FFN_XN = NBF * FFN_CHUNK, FFN_H = FFN_XN + 8192, FFN_RED = FFN_H + 5504, FFN_BAR = FFN_RED + 32768;
constexpr int SMEM_FFN = FFN_BAR + 64;
static_assert(FFN_CHUNK == 43 * DM * 2, "chunk geometry");
constexpr int SMEM_BYTES = SMEM_ATT > SMEM_FFN ? SMEM_ATT : SMEM_FFN;

__device__ __align__(256) uint4 g_q_part[NH * NB * 32];
__device__ __align__(256) uint4 g_attn_part[NB * 32 * NH * 8];
__device__ __align__(256) uint4 g_ffn_part[NB * 32 * N_FFN * 8];
__device__ __align__(256) uint32_t g_progress[64];
#define FK_ONE4 1u, 1u, 1u, 1u
#define FK_ONE16 FK_ONE4, FK_ONE4, FK_ONE4, FK_ONE4
#define FK_ONE64 FK_ONE16, FK_ONE16, FK_ONE16, FK_ONE16
__device__ __align__(256) uint32_t g_epoch[N_CTA] = {FK_ONE64, FK_ONE64, FK_ONE4};

__device__ __forceinline__ uint32_t smem_u32(const void* p) { return (uint32_t)__cvta_generic_to_shared(p); }

__device__ __forceinline__ void mbar_init(uint32_t bar, uint32_t cnt) {
    asm volatile("mbarrier.init.shared::cta.b64 [%0], %1;" :: "r"(bar), "r"(cnt) : "memory");
}
__device__ __forceinline__ void mbar_expect_tx(uint32_t bar, uint32_t bytes) {
    asm volatile("mbarrier.arrive.expect_tx.shared::cta.b64 _, [%0], %1;" :: "r"(bar), "r"(bytes) : "memory");
}
__device__ __forceinline__ uint32_t atom_inc_shared(uint32_t addr) {
    uint32_t old;
    asm volatile("atom.relaxed.cta.shared::cta.add.u32 %0, [%1], 1;" : "=r"(old) : "r"(addr) : "memory");
    return old;
}
__device__ __forceinline__ void mbar_wait(uint32_t bar, uint32_t parity) {
    asm volatile(
        "{\n"
        ".reg .pred p;\n"
        "FK_WAIT:\n"
        "mbarrier.try_wait.parity.shared::cta.b64 p, [%0], %1;\n"
        "@p bra FK_DONE;\n"
        "bra FK_WAIT;\n"
        "FK_DONE:\n"
        "}\n" :: "r"(bar), "r"(parity) : "memory");
}
__device__ __forceinline__ void bulk_load(uint32_t dst, const void* src, uint32_t bytes, uint32_t bar, uint64_t pol) {
    asm volatile("cp.async.bulk.shared::cluster.global.mbarrier::complete_tx::bytes.L2::cache_hint [%0], [%1], %2, [%3], %4;"
                 :: "r"(dst), "l"(src), "r"(bytes), "r"(bar), "l"(pol) : "memory");
}
__device__ __forceinline__ uint4 ldg_nc(const void* p) {
    uint4 v;
    asm volatile("ld.global.nc.L1::no_allocate.v4.u32 {%0,%1,%2,%3}, [%4];"
                 : "=r"(v.x), "=r"(v.y), "=r"(v.z), "=r"(v.w) : "l"(p));
    return v;
}
__device__ __forceinline__ void bulk_load_plain(uint32_t dst, const void* src, uint32_t bytes, uint32_t bar) {
    asm volatile("cp.async.bulk.shared::cluster.global.mbarrier::complete_tx::bytes [%0], [%1], %2, [%3];"
                 :: "r"(dst), "l"(src), "r"(bytes), "r"(bar) : "memory");
}
__device__ __forceinline__ uint32_t ldg_nc32(const void* p) {
    uint32_t v;
    asm volatile("ld.global.nc.L1::no_allocate.u32 %0, [%1];" : "=r"(v) : "l"(p));
    return v;
}
__device__ __forceinline__ uint32_t lds32(uint32_t addr) {
    uint32_t v;
    asm volatile("ld.volatile.shared.u32 %0, [%1];" : "=r"(v) : "r"(addr) : "memory");
    return v;
}
__device__ __forceinline__ uint32_t pin(uint32_t v) {
    uint32_t r;
    asm volatile("mov.b32 %0, %1;" : "=r"(r) : "r"(v));
    return r;
}
__device__ __forceinline__ uint32_t ld_relaxed32(const uint32_t* p) {
    uint32_t v;
    asm volatile("ld.relaxed.gpu.global.u32 %0, [%1];" : "=r"(v) : "l"(p) : "memory");
    return v;
}
__device__ __forceinline__ bool mbar_test(uint32_t bar, uint32_t parity) {
    uint32_t ok;
    asm volatile("{\n.reg .pred p;\nmbarrier.test_wait.parity.shared::cta.b64 p, [%1], %2;\nselp.u32 %0, 1, 0, p;\n}\n"
                 : "=r"(ok) : "r"(bar), "r"(parity) : "memory");
    return ok != 0;
}
__device__ __forceinline__ uint4 ld_relaxed(const uint4* p) {
    uint4 v;
    asm volatile("ld.relaxed.gpu.global.v4.u32 {%0,%1,%2,%3}, [%4];"
                 : "=r"(v.x), "=r"(v.y), "=r"(v.z), "=r"(v.w) : "l"(p) : "memory");
    return v;
}
__device__ __forceinline__ void st_relaxed(uint4* p, uint4 v) {
    asm volatile("st.relaxed.gpu.global.v4.u32 [%0], {%1,%2,%3,%4};"
                 :: "l"(p), "r"(v.x), "r"(v.y), "r"(v.z), "r"(v.w) : "memory");
}
__device__ __forceinline__ void ldsm_x4(uint32_t (&r)[4], uint32_t addr) {
    asm volatile("ldmatrix.sync.aligned.m8n8.x4.shared.b16 {%0,%1,%2,%3}, [%4];"
                 : "=r"(r[0]), "=r"(r[1]), "=r"(r[2]), "=r"(r[3]) : "r"(addr) : "memory");
}
__device__ __forceinline__ void ldsm_x4_t(uint32_t (&r)[4], uint32_t addr) {
    asm volatile("ldmatrix.sync.aligned.m8n8.x4.trans.shared.b16 {%0,%1,%2,%3}, [%4];"
                 : "=r"(r[0]), "=r"(r[1]), "=r"(r[2]), "=r"(r[3]) : "r"(addr) : "memory");
}
__device__ __forceinline__ void mma_bf16(float (&c)[4], const uint32_t (&a)[4], uint32_t b0, uint32_t b1) {
    asm volatile("mma.sync.aligned.m16n8k16.row.col.f32.bf16.bf16.f32 {%0,%1,%2,%3}, {%4,%5,%6,%7}, {%8,%9}, {%0,%1,%2,%3};"
                 : "+f"(c[0]), "+f"(c[1]), "+f"(c[2]), "+f"(c[3])
                 : "r"(a[0]), "r"(a[1]), "r"(a[2]), "r"(a[3]), "r"(b0), "r"(b1));
}
__device__ __forceinline__ float ex2(float x) {
    float r;
    asm("ex2.approx.ftz.f32 %0, %1;" : "=f"(r) : "f"(x));
    return r;
}
__device__ __forceinline__ uint32_t pack_bf16(float lo, float hi) {
    uint32_t r;
    asm("cvt.rn.bf16x2.f32 %0, %1, %2;" : "=r"(r) : "f"(hi), "f"(lo));
    return r;
}
__device__ __forceinline__ float bf_lo(uint32_t w) { return __uint_as_float(w << 16); }
__device__ __forceinline__ float bf_hi(uint32_t w) { return __uint_as_float(w & 0xffff0000u); }
__device__ __forceinline__ float bf16r(float x) { return __bfloat162float(__float2bfloat16_rn(x)); }
__device__ __forceinline__ float silu_f(float x) { return x / (1.0f + __expf(-x)); }

__device__ __forceinline__ void warp_layernorm(const uint4 a, const uint4 b, float (&xn)[16]) {
    float v[16];
    v[0] = bf_lo(a.x); v[1] = bf_hi(a.x); v[2] = bf_lo(a.y); v[3] = bf_hi(a.y);
    v[4] = bf_lo(a.z); v[5] = bf_hi(a.z); v[6] = bf_lo(a.w); v[7] = bf_hi(a.w);
    v[8] = bf_lo(b.x); v[9] = bf_hi(b.x); v[10] = bf_lo(b.y); v[11] = bf_hi(b.y);
    v[12] = bf_lo(b.z); v[13] = bf_hi(b.z); v[14] = bf_lo(b.w); v[15] = bf_hi(b.w);
    float s = 0.f;
#pragma unroll
    for (int i = 0; i < 16; i++) s += v[i];
#pragma unroll
    for (int o = 16; o; o >>= 1) s += __shfl_xor_sync(0xffffffffu, s, o);
    const float mean = s * (1.0f / DM);
    float ss = 0.f;
#pragma unroll
    for (int i = 0; i < 16; i++) { const float d = v[i] - mean; ss = fmaf(d, d, ss); }
#pragma unroll
    for (int o = 16; o; o >>= 1) ss += __shfl_xor_sync(0xffffffffu, ss, o);
    const float m_bf = bf16r(mean);
    const float den = bf16r(sqrtf(bf16r(bf16r(ss * (1.0f / DM)) + 1e-5f)));
#pragma unroll
    for (int i = 0; i < 16; i++) xn[i] = bf16r(__fdiv_rn(bf16r(v[i] - m_bf), den));
}

__device__ __forceinline__ bool ll_valid(const uint4& v, uint32_t tag) { return v.y == tag && v.w == tag; }

__device__ __forceinline__ void ffn_cta(uint8_t* smem, int f, uint32_t tag,
                                        const __nv_bfloat16* __restrict__ x,
                                        const __nv_bfloat16* __restrict__ w1,
                                        const __nv_bfloat16* __restrict__ w2) {
    const int tid = threadIdx.x, warp = tid >> 5, lane = tid & 31;
    const uint32_t sbase = smem_u32(smem), bar = sbase + FFN_BAR;
    float* xnT = reinterpret_cast<float*>(smem + FFN_XN);
    float* hT  = reinterpret_cast<float*>(smem + FFN_H);
    float* red = reinterpret_cast<float*>(smem + FFN_RED);
    if (tid == 0) {
#pragma unroll
        for (int s = 0; s < NBF; s++) mbar_init(bar + s * 8, 1);
    }
    __syncthreads();
    auto issue = [&](int c) {
        const int s = c % NBF;
        if (tid == 0) mbar_expect_tx(bar + s * 8, FFN_CHUNK);
        if (c < 8) {
            __syncthreads();
            if (tid < 64) bulk_load_plain(sbase + s * FFN_CHUNK + tid * (FS * 2), w1 + (size_t)(c * 64 + tid) * FF + f * FS, FS * 2, bar + s * 8);
        } else if (tid == 0) {
            bulk_load_plain(sbase + s * FFN_CHUNK, w2 + (size_t)(f * FS + (c - 8) * 43) * DM, FFN_CHUNK, bar + s * 8);
        }
    };
    for (int c = 0; c < NBF; c++) issue(c);
    if (warp < NB) {
        float xn[16];
        const uint4 xa = ldg_nc(x + warp * DM + lane * 16), xb = ldg_nc(x + warp * DM + lane * 16 + 8);
        warp_layernorm(xa, xb, xn);
#pragma unroll
        for (int i = 0; i < 16; i++) xnT[(lane * 16 + i) * 4 + warp] = xn[i];
    }
    __syncthreads();
    float acc[4][8];
#pragma unroll
    for (int b = 0; b < 4; b++)
#pragma unroll
        for (int c = 0; c < 8; c++) acc[b][c] = 0.f;
#pragma unroll 1
    for (int c = 0; c < 16; c++) {
        const int s = c % NBF;
        mbar_wait(bar + s * 8, (c / NBF) & 1);
        const bool st1 = c < 8;
        const int cg = st1 ? tid % 43 : (tid & 63), r0 = st1 ? tid / 43 : (tid >> 6);
        const int rstep = st1 ? 5 : 4, nrows = st1 ? 64 : 43, rbytes = st1 ? FS * 2 : DM * 2;
        const float* vec = st1 ? xnT + c * 64 * 4 : hT + (c - 8) * 43 * 4;
        const uint8_t* wb = smem + s * FFN_CHUNK + cg * 16;
        if (!st1 || tid < 43 * 5) {
#pragma unroll 2
            for (int k = r0; k < nrows; k += rstep) {
                const uint4 w = *reinterpret_cast<const uint4*>(wb + k * rbytes);
                const float4 xv = *reinterpret_cast<const float4*>(vec + k * 4);
                const float wf[8] = {bf_lo(w.x), bf_hi(w.x), bf_lo(w.y), bf_hi(w.y), bf_lo(w.z), bf_hi(w.z), bf_lo(w.w), bf_hi(w.w)};
#pragma unroll
                for (int j = 0; j < 8; j++) {
                    acc[0][j] = fmaf(xv.x, wf[j], acc[0][j]);
                    acc[1][j] = fmaf(xv.y, wf[j], acc[1][j]);
                    acc[2][j] = fmaf(xv.z, wf[j], acc[2][j]);
                    acc[3][j] = fmaf(xv.w, wf[j], acc[3][j]);
                }
            }
        }
        __syncthreads();
        if (c + NBF < 16) issue(c + NBF);
        if (c == 7) {
            if (tid < 43 * 5) {
#pragma unroll
                for (int b = 0; b < 4; b++)
#pragma unroll
                    for (int j = 0; j < 8; j++) red[(r0 * 4 + b) * FS + cg * 8 + j] = acc[b][j];
            }
#pragma unroll
            for (int b = 0; b < 4; b++)
#pragma unroll
                for (int j = 0; j < 8; j++) acc[b][j] = 0.f;
            __syncthreads();
            for (int i = tid; i < 4 * FS; i += NTHREADS) {
                const int b = i / FS, cc = i % FS;
                float sum = 0.f;
#pragma unroll
                for (int ks = 0; ks < 5; ks++) sum += red[(ks * 4 + b) * FS + cc];
                hT[cc * 4 + b] = bf16r(silu_f(bf16r(sum)));
            }
            __syncthreads();
        }
    }
    {
        const int cg = tid & 63, fs = tid >> 6;
#pragma unroll
        for (int b = 0; b < 4; b++)
#pragma unroll
            for (int j = 0; j < 8; j++) red[(fs * 4 + b) * DM + cg * 8 + j] = acc[b][j];
    }
    __syncthreads();
    for (int i = tid; i < NB * 256; i += NTHREADS) {
        const int b = i >> 8, j = (i >> 3) & 31, p = i & 7;
        float s0 = 0.f, s1 = 0.f;
#pragma unroll
        for (int fs = 0; fs < 4; fs++) { s0 += red[(fs * 4 + b) * DM + 16 * j + p]; s1 += red[(fs * 4 + b) * DM + 16 * j + 8 + p]; }
        st_relaxed(&g_ffn_part[((b * 32 + j) * N_FFN + f) * 8 + p],
                   make_uint4(__float_as_uint(s0), tag, __float_as_uint(s1), tag));
    }
}

__device__ __forceinline__ uint4 ld_relaxed_if(const uint4* p, uint4 v, uint32_t pred) {
    asm volatile("{\n.reg .pred p;\nsetp.ne.u32 p, %5, 0;\n@p ld.relaxed.gpu.global.v4.u32 {%0,%1,%2,%3}, [%4];\n}\n"
                 : "+r"(v.x), "+r"(v.y), "+r"(v.z), "+r"(v.w) : "l"(p), "r"(pred) : "memory");
    return v;
}
__device__ __noinline__ void final_reduce(const uint4* p, uint32_t tag, float x0, float x1, float g0, float g1,
                                          uint32_t* out16, uint32_t live) {
    const int lane = threadIdx.x & 31;
    uint4 v[8];
#pragma unroll
    for (int i = 0; i < 8; i++) v[i] = ld_relaxed_if(p + i * 8, make_uint4(0, tag, 0, tag), live);
    for (int spin = 0; spin < (1 << 20); spin++) {
        bool ok = true;
#pragma unroll
        for (int i = 0; i < 8; i++) {
            const bool miss = !ll_valid(v[i], tag);
            v[i] = ld_relaxed_if(p + i * 8, v[i], miss);
            ok = ok && !miss;
        }
        if (ok) break;
    }
    __syncwarp();
    float s0 = ((__uint_as_float(v[0].x) + __uint_as_float(v[1].x)) + (__uint_as_float(v[2].x) + __uint_as_float(v[3].x)))
             + ((__uint_as_float(v[4].x) + __uint_as_float(v[5].x)) + (__uint_as_float(v[6].x) + __uint_as_float(v[7].x)));
    float s1 = ((__uint_as_float(v[0].z) + __uint_as_float(v[1].z)) + (__uint_as_float(v[2].z) + __uint_as_float(v[3].z)))
             + ((__uint_as_float(v[4].z) + __uint_as_float(v[5].z)) + (__uint_as_float(v[6].z) + __uint_as_float(v[7].z)));
    s0 += __shfl_xor_sync(0xffffffffu, s0, 8);  s1 += __shfl_xor_sync(0xffffffffu, s1, 8);
    s0 += __shfl_xor_sync(0xffffffffu, s0, 16); s1 += __shfl_xor_sync(0xffffffffu, s1, 16);
    const float o0 = x0 + bf16r(bf16r(s0) * g0), o1 = x1 + bf16r(bf16r(s1) * g1);
    const int src = (2 * lane) & 7;
    const float a0 = __shfl_sync(0xffffffffu, o0, src), a1 = __shfl_sync(0xffffffffu, o0, src + 1);
    const float b0 = __shfl_sync(0xffffffffu, o1, src), b1 = __shfl_sync(0xffffffffu, o1, src + 1);
    const uint32_t w = lane < 4 ? pack_bf16(a0, a1) : pack_bf16(b0, b1);
    asm volatile("{\n.reg .pred p;\nsetp.ne.u32 p, %2, 0;\n@p st.global.u32 [%0], %1;\n}\n"
                 :: "l"(out16 + (lane & 7)), "r"(w), "r"((uint32_t)(live && lane < 8)) : "memory");
}

__global__ void __launch_bounds__(NTHREADS, 1)
fused_decode_kernel(const __nv_bfloat16* __restrict__ x, const __nv_bfloat16* __restrict__ Kc,
                    const __nv_bfloat16* __restrict__ Vc, const __nv_bfloat16* __restrict__ wq,
                    const __nv_bfloat16* __restrict__ wo, const __nv_bfloat16* __restrict__ w1,
                    const __nv_bfloat16* __restrict__ w2, __nv_bfloat16* __restrict__ out) {
    extern __shared__ __align__(1024) uint8_t smem[];
    const int cta = blockIdx.x;
    const int tid = threadIdx.x, warp = tid >> 5, lane = tid & 31;
    if (cta >= N_ATT) {
        const uint32_t tag = ld_relaxed32(&g_epoch[cta]);
        ffn_cta(smem, cta - N_ATT, tag, x, w1, w2);
        if (tid == 0) { g_epoch[cta] = tag + 1; }
        return;
    }

    const int b = cta & 3, h = cta >> 2;
    const int bh = b * NH + h;
    const uint32_t sbase = pin(smem_u32(smem));
    const uint32_t bar_full = sbase + OFF_BAR;
    const uint32_t cnt_rel = bar_full + NST * 8;
    const char* kp = reinterpret_cast<const char*>(Kc) + (size_t)bh * SK * DH * 2;
    const char* vp = reinterpret_cast<const char*>(Vc) + (size_t)bh * SK * DH * 2;
    const char* wop = reinterpret_cast<const char*>(wo) + (size_t)h * DH * DM * 2;
    uint64_t pol;
    asm volatile("createpolicy.fractional.L2::evict_first.b64 %0, 1.0;" : "=l"(pol));
    auto issue_kv = [&](const char* src, int s) {
        const uint32_t bar = bar_full + s * 8;
        mbar_expect_tx(bar, STAGE_BYTES);
        bulk_load(sbase + s * STAGE_BYTES, src, STAGE_BYTES, bar, pol);
    };
    auto issue_first = [&](int n) { issue_kv(((n & 1) ? vp : kp) + (size_t)(n >> 1) * STAGE_BYTES, n); };
    const uint32_t bar_w = bar_full + 216, cnt_w = bar_full + 224;
    auto issue_w = [&](int q) {
        mbar_expect_tx(bar_w, STAGE_BYTES);
        bulk_load_plain(sbase + OFF_W, wop + (size_t)q * STAGE_BYTES, STAGE_BYTES, bar_w);
    };

    const int g = lane >> 2, t = lane & 3;
    float* xn_s  = reinterpret_cast<float*>(smem + OFF_XN);
    float* red_s = reinterpret_cast<float*>(smem + OFF_RED);
    __nv_bfloat16* q_s = reinterpret_cast<__nv_bfloat16*>(smem + OFF_Q);
    float* ml_s = reinterpret_cast<float*>(smem + OFF_ML);
    __nv_bfloat16* o_s = reinterpret_cast<__nv_bfloat16*>(smem + OFF_O);

    uint4* const q_out = &g_q_part[(h * NB + (lane >> 3)) * 32 + b * 8 + (lane & 7)];
    uint4* const a_out = &g_attn_part[((b * 32 + warp * 4 + t) * NH + h) * 8 + g];

    volatile uint32_t* q_flag = reinterpret_cast<volatile uint32_t*>(smem + OFF_BAR + 192);
    const uint32_t bar_x = bar_full + 200;
    if (tid == 0) {
        mbar_init(bar_full, 1);
        issue_first(0);
        mbar_init(bar_x, 1);
        mbar_expect_tx(bar_x, NB * DM * 2);
        bulk_load_plain(sbase + OFF_X, x, NB * DM * 2, bar_x);
#pragma unroll
        for (int s = 1; s < NST; s++) mbar_init(bar_full + s * 8, 1);
        mbar_init(bar_w, 1);
#pragma unroll
        for (int s = 0; s < NST; s++) *reinterpret_cast<volatile uint32_t*>(smem + OFF_BAR + NST * 8 + s * 4) = 0;
        *reinterpret_cast<volatile uint32_t*>(smem + OFF_BAR + 224) = 0;
        *q_flag = 0;
#pragma unroll 1
        for (int s = 1; s < FK_PRE; s++) issue_first(s);
    }
    uint32_t qf[8][2];
    uint32_t tag;
    {
        uint32_t w[32];
        const __nv_bfloat16* wp = wq + (size_t)(warp * 64 + (lane >> 4) * 32) * (NH * DH) + h * DH + b * 32 + (lane & 15) * 2;
#pragma unroll
        for (int i = 0; i < 32; i++) w[i] = ldg_nc32(wp + (size_t)i * (NH * DH));
        tag = ld_relaxed32(&g_epoch[cta]);
        if (tid == 0) {
#pragma unroll 1
            for (int s = FK_PRE; s < FK_FIRST; s++) issue_first(s);
            asm volatile("prefetch.global.L2 [%0];" :: "l"(wop));
        }
        if (warp == 0) st_relaxed(q_out, make_uint4(0, 0, 0, 0));
        if (FK_INIT_AT < 0) st_relaxed(a_out, make_uint4(0, 0, 0, 0));
        __syncthreads();
        if (warp < 4) {
            float xn[16];
            mbar_wait(bar_x, 0);
            const uint4 xa = *reinterpret_cast<const uint4*>(smem + OFF_X + warp * DM * 2 + lane * 32);
            const uint4 xb = *reinterpret_cast<const uint4*>(smem + OFF_X + warp * DM * 2 + lane * 32 + 16);
            warp_layernorm(xa, xb, xn);
#pragma unroll
            for (int i = 0; i < 16; i += 4)
                *reinterpret_cast<float4*>(xn_s + warp * DM + lane * 16 + i) = make_float4(xn[i], xn[i + 1], xn[i + 2], xn[i + 3]);
        }
        __syncthreads();
        float acc[4][2];
#pragma unroll
        for (int bb = 0; bb < 4; bb++) acc[bb][0] = acc[bb][1] = 0.f;
        const float* xp = xn_s + warp * 64 + (lane >> 4) * 32;
#pragma unroll
        for (int i4 = 0; i4 < 8; i4++) {
#pragma unroll
            for (int bb = 0; bb < 4; bb++) {
                const float4 xv = *reinterpret_cast<const float4*>(xp + bb * DM + i4 * 4);
                const float xs[4] = {xv.x, xv.y, xv.z, xv.w};
#pragma unroll
                for (int u = 0; u < 4; u++) {
                    acc[bb][0] = fmaf(xs[u], bf_lo(w[i4 * 4 + u]), acc[bb][0]);
                    acc[bb][1] = fmaf(xs[u], bf_hi(w[i4 * 4 + u]), acc[bb][1]);
                }
            }
        }
        const bool up = lane >= 16;
        float k0 = up ? acc[2][0] : acc[0][0], k1 = up ? acc[2][1] : acc[0][1];
        float k2 = up ? acc[3][0] : acc[1][0], k3 = up ? acc[3][1] : acc[1][1];
        k0 += __shfl_xor_sync(0xffffffffu, up ? acc[0][0] : acc[2][0], 16);
        k1 += __shfl_xor_sync(0xffffffffu, up ? acc[0][1] : acc[2][1], 16);
        k2 += __shfl_xor_sync(0xffffffffu, up ? acc[1][0] : acc[3][0], 16);
        k3 += __shfl_xor_sync(0xffffffffu, up ? acc[1][1] : acc[3][1], 16);
        float* rp = red_s + warp * 128 + (up ? 64 : 0) + (lane & 15) * 2;
        *reinterpret_cast<float2*>(rp)      = make_float2(k0, k1);
        *reinterpret_cast<float2*>(rp + 32) = make_float2(k2, k3);
        __syncthreads();
        if (warp == 0) {
            float4 s = make_float4(0.f, 0.f, 0.f, 0.f);
#pragma unroll
            for (int w8 = 0; w8 < NCW; w8++) {
                const float4 v = *reinterpret_cast<const float4*>(red_s + w8 * 128 + lane * 4);
                s.x += v.x; s.y += v.y; s.z += v.z; s.w += v.w;
            }
            st_relaxed(q_out, make_uint4(pack_bf16(s.x, s.y), tag, pack_bf16(s.z, s.w), tag));
            const uint4* p = &g_q_part[(h * NB + b) * 32 + lane];
            uint4 v = ld_relaxed(p);
            for (int spin = 0; !ll_valid(v, tag) && spin < (1 << 20); spin++) v = ld_relaxed(p);
            *reinterpret_cast<uint2*>(q_s + lane * 4) = make_uint2(v.x, v.z);
            if (lane == 0) *q_flag = 1;
        }
        if (FK_DRY && warp == 1) final_reduce(g_attn_part, tag, 0.f, 0.f, 0.f, 0.f, reinterpret_cast<uint32_t*>(out), 0);
        if (tid == NTHREADS - 32) {
            int next = FK_FIRST, watch = 0;
            while (next < NST) {
                if (mbar_test(bar_full + watch * 8, 0)) { issue_first(next); next++; watch++; }
                else if (*q_flag) break;
            }
#pragma unroll 1
            for (; next < NST; next++) issue_first(next);
        }
        __syncthreads();
#pragma unroll
        for (int j = 0; j < 8; j++) {
            const int c = (j ^ g) & 7;
            qf[j][0] = *reinterpret_cast<const uint32_t*>(q_s + c * 8 + 2 * t);
            qf[j][1] = *reinterpret_cast<const uint32_t*>(q_s + 64 + c * 8 + 2 * t);
        }
    }

    constexpr float RSQRT_DH = 0.08838834764831845f, LOG2E = 1.4426950408889634f;
    const int li = lane & 7, lm = lane >> 3;
    const uint32_t k_base = pin(sbase + (uint32_t)((warp * 16 + li + 8 * (lm & 1)) * 256 + (lm >> 1) * 128 + li * 16));
    const uint32_t v_base = pin(sbase + (uint32_t)((warp * 16 + li + 8 * (lm >> 1)) * 256 + (lm & 1) * 128 + li * 16));
    const bool diag = (t == (g >> 1));
    uint32_t msk[8];
#pragma unroll
    for (int j = 0; j < 8; j++) msk[j] = pin((j == (g ^ (2 * t)) ? 0x0000ffffu : 0u) | (j == (g ^ (2 * t) ^ 1) ? 0xffff0000u : 0u));
    const uint32_t ones[4] = {0x3f803f80u, 0x3f803f80u, 0x3f803f80u, 0x3f803f80u};

    float acc0[4] = {0.f, 0.f, 0.f, 0.f}, acc1[4] = {0.f, 0.f, 0.f, 0.f}, lacc[4] = {0.f, 0.f, 0.f, 0.f};
    float m_raw = -INFINITY;
    float m_run = -INFINITY, mc = 0.f;
    float fin_scale = 0.f;
    int st = 0; uint32_t ph = 0;
    int seq = NST;
    uint32_t wa[8][4][4];
    float g0 = 0.f, g1 = 0.f;
    uint4 gv = make_uint4(0, 0, 0, 0);
    const int cp = lane & 7, q4 = lane >> 3;
    const float x0 = __bfloat162float(reinterpret_cast<const __nv_bfloat16*>(smem + OFF_X)[b * DM + h * 16 + cp]);
    const float x1 = __bfloat162float(reinterpret_cast<const __nv_bfloat16*>(smem + OFF_X)[b * DM + h * 16 + 8 + cp]);
    const uint32_t prog_base = (tag - 1) * (uint32_t)(N_ATT * NT);
    const uint32_t prog_s = bar_full + 208;
    uint32_t prog_v = prog_base;
    if (tid == 0) *reinterpret_cast<volatile uint32_t*>(smem + OFF_BAR + 208) = prog_base;
    __syncthreads();
    auto pace = [&](uint32_t pv, uint32_t lim) {
        for (int spin = 0; (int)(pv - lim) < 0 && spin < 4096; spin++) pv = ld_relaxed32(&g_progress[0]);
    };

#pragma unroll 1
    for (int it = 0; it < NT; it++) {
#pragma unroll
        for (int q = 0; q <= 4; q++) {
            if (it == FK_WTILE + q * FK_WSTEP) {
                if (q == 0) {
                    if (tid == 0) {
                        asm volatile("fence.proxy.async.shared::cta;" ::: "memory");
                        issue_w(0);
                    }
                } else {
                    mbar_wait(bar_w, (q - 1) & 1);
                    const uint32_t wb = sbase + OFF_W + (li + 8 * (lane >> 4)) * 1024 + warp * 128 + (lm & 1) * 16;
#pragma unroll
                    for (int j = 0; j < 4; j++) {
                        ldsm_x4_t(wa[2 * q - 2][j], wb + j * 32);
                        ldsm_x4_t(wa[2 * q - 1][j], wb + 16384 + j * 32);
                    }
                    if (q < 4 && lane == 0) {
                        const uint32_t rel = atom_inc_shared(cnt_w);
                        if ((rel & (NCW - 1)) == NCW - 1) issue_w(q);
                    }
                }
                __syncwarp();
            }
        }
        if (it == FK_INIT_AT) st_relaxed(a_out, make_uint4(0, 0, 0, 0));
        if (it == NT - 12 && warp == 0) {
            gv = ld_relaxed(&g_ffn_part[((b * 32 + h) * N_FFN + q4) * 8 + cp]);
        }
        if (it == NT - 2 && warp == 0) {
            const uint4* p = &g_ffn_part[((b * 32 + h) * N_FFN + q4) * 8 + cp];
            uint4 v = gv;
            for (int spin = 0; !ll_valid(v, tag) && spin < (1 << 20); spin++) { __nanosleep(64); v = ld_relaxed(p); }
            __syncwarp();
            g0 = __uint_as_float(v.x); g1 = __uint_as_float(v.z);
            g0 += __shfl_xor_sync(0xffffffffu, g0, 8);  g1 += __shfl_xor_sync(0xffffffffu, g1, 8);
            g0 += __shfl_xor_sync(0xffffffffu, g0, 16); g1 += __shfl_xor_sync(0xffffffffu, g1, 16);
            g0 = bf16r(silu_f(bf16r(g0))); g1 = bf16r(silu_f(bf16r(g1)));
        }
        if (tid == 0) {
            *reinterpret_cast<volatile uint32_t*>(smem + OFF_BAR + 208) = prog_v;
            prog_v = ld_relaxed32(&g_progress[0]);
        }
        const bool endgame = it >= NT - FK_ENDT;
        const char* k_next = kp + (size_t)(it + NST / 2) * STAGE_BYTES;
        const char* v_next = vp + (size_t)(it + NST / 2) * STAGE_BYTES;
        mbar_wait(bar_full + st * 8, ph);
        float c0[4] = {0.f, 0.f, 0.f, 0.f}, c1[4] = {0.f, 0.f, 0.f, 0.f};
        uint32_t relK = 0, pvK = 0;
        const uint32_t kb = k_base + st * STAGE_BYTES;
        {
#pragma unroll
            for (int j = 0; j < 8; j++) {
                uint32_t a[4];
                ldsm_x4(a, kb ^ (j << 4));
                mma_bf16((j & 1) ? c1 : c0, a, qf[j][0], qf[j][1]);
            }
            if (!endgame && seq < NSEQ && lane == 0) {
                relK = atom_inc_shared(cnt_rel + st * 4);
                pvK = lds32(prog_s);
            }
        }
        const float u0 = (g & 1) ? (c0[1] + c1[1]) : (c0[0] + c1[0]);
        const float u1 = (g & 1) ? (c0[3] + c1[3]) : (c0[2] + c1[2]);
        int key = __float_as_int(diag ? fmaxf(u0, u1) : -INFINITY);
        key ^= (key >> 31) & 0x7fffffff;
        key = __reduce_max_sync(0xffffffffu, key);
        const uint32_t r1 = pack_bf16(u0, u1);
        const uint32_t r2 = pack_bf16(bf_lo(r1) * RSQRT_DH, bf_hi(r1) * RSQRT_DH);
        const float s0 = diag ? bf_lo(r2) : -INFINITY, s1 = diag ? bf_hi(r2) : -INFINITY;
        key ^= (key >> 31) & 0x7fffffff;
        const float tmax = __int_as_float(key);
        if (tmax > m_raw) {
            m_raw = tmax;
            const float m_new = bf16r(bf16r(tmax) * RSQRT_DH);
            const float sc = ex2((m_run - m_new) * LOG2E);
#pragma unroll
            for (int i = 0; i < 4; i++) { acc0[i] *= sc; acc1[i] *= sc; }
            lacc[0] *= sc;
            m_run = m_new;
            mc = -m_new * LOG2E;
        }
        const uint32_t pk = pack_bf16(ex2(fmaf(s0, LOG2E, mc)), ex2(fmaf(s1, LOG2E, mc)));
        const uint32_t xx = __shfl_sync(0xffffffffu, pk, 9 * t), yy = __shfl_sync(0xffffffffu, pk, 9 * t + 4);
        const uint32_t pp0 = __byte_perm(xx, yy, 0x5410), pp1 = __byte_perm(xx, yy, 0x7632);
        if ((relK & (NCW - 1)) == NCW - 1) {
            pace(pvK, prog_base + (uint32_t)(it * N_ATT - (FK_LEAD)));
            issue_kv(k_next, st);
        }
        __syncwarp();
        const int stK = st;
        seq++;
        if (++st == NST) { st = 0; ph ^= 1; }
        mma_bf16(lacc, ones, pp0, pp1);
        if (it == NT - 1) {
            if (lane == 0) { ml_s[warp] = m_run; ml_s[8 + warp] = lacc[0]; }
            __syncthreads();
            const float4 ma = *reinterpret_cast<const float4*>(ml_s), mb = *reinterpret_cast<const float4*>(ml_s + 4);
            const float4 la = *reinterpret_cast<const float4*>(ml_s + 8), lb = *reinterpret_cast<const float4*>(ml_s + 12);
            const float M = fmaxf(fmaxf(fmaxf(ma.x, ma.y), fmaxf(ma.z, ma.w)), fmaxf(fmaxf(mb.x, mb.y), fmaxf(mb.z, mb.w)));
            const float L = (ex2((ma.x - M) * LOG2E) * la.x + ex2((ma.y - M) * LOG2E) * la.y) + (ex2((ma.z - M) * LOG2E) * la.z + ex2((ma.w - M) * LOG2E) * la.w)
                          + (ex2((mb.x - M) * LOG2E) * lb.x + ex2((mb.y - M) * LOG2E) * lb.y) + (ex2((mb.z - M) * LOG2E) * lb.z + ex2((mb.w - M) * LOG2E) * lb.w);
            fin_scale = __fdividef(ex2((m_run - M) * LOG2E), L);
        }
        mbar_wait(bar_full + st * 8, ph);
        const uint32_t vb = v_base + st * STAGE_BYTES;
        {
            uint32_t relV = 0, pvV = 0;
#pragma unroll
            for (int j = 0; j < 8; j++) {
                uint32_t a[4];
                ldsm_x4_t(a, vb ^ (j << 4));
                mma_bf16((j & 1) ? acc1 : acc0, a, pp0 & msk[j], pp1 & msk[j]);
            }
            if (seq - (endgame ? 1 : 0) < NSEQ && lane == 0) {
                relV = atom_inc_shared(cnt_rel + st * 4);
                pvV = lds32(prog_s);
            }
            if (tid == NTHREADS - 32) asm volatile("red.relaxed.gpu.global.add.u32 [%0], 1;" :: "l"(&g_progress[0]) : "memory");
            if ((relV & (NCW - 1)) == NCW - 1) {
                if (endgame) {
                    pace(pvV, prog_base + (uint32_t)((it + 1) * N_ATT - (FK_LEAD_END)));
                    issue_kv(k_next, stK);
                }
                if (seq < NSEQ) issue_kv(v_next, st);
            }
        }
        __syncwarp();
        seq++;
        if (++st == NST) { st = 0; ph ^= 1; }
    }

    {
        float* o = red_s + warp * 128;
        o[16 * t + g]          = (acc0[0] + acc1[0]) * fin_scale;
        o[16 * t + 8 + g]      = (acc0[1] + acc1[1]) * fin_scale;
        o[64 + 16 * t + g]     = (acc0[2] + acc1[2]) * fin_scale;
        o[64 + 16 * t + 8 + g] = (acc0[3] + acc1[3]) * fin_scale;
    }
    __syncthreads();
    if (tid < DH) {
        float v[8];
#pragma unroll
        for (int w = 0; w < 8; w++) v[w] = red_s[w * 128 + tid];
        const float o = ((v[0] + v[1]) + (v[2] + v[3])) + ((v[4] + v[5]) + (v[6] + v[7]));
        o_s[((tid >> 1) & 3) * 32 + (tid >> 4) * 4 + ((tid >> 3) & 1) * 2 + (tid & 1)] = __float2bfloat16_rn(o);
    }
    __syncthreads();
    {
        float d[4][4];
#pragma unroll
        for (int j = 0; j < 4; j++) { d[j][0] = d[j][1] = d[j][2] = d[j][3] = 0.f; }
        uint4 ov[4];
#pragma unroll
        for (int i = 0; i < 4; i++) ov[i] = *reinterpret_cast<const uint4*>(o_s + t * 32 + i * 8);
#pragma unroll
        for (int i = 0; i < 4; i++) {
#pragma unroll
            for (int j = 0; j < 4; j++) mma_bf16(d[j], wa[2 * i][j], ov[i].x, ov[i].y);
#pragma unroll
            for (int j = 0; j < 4; j++) mma_bf16(d[j], wa[2 * i + 1][j], ov[i].z, ov[i].w);
        }
        float r0 = d[0][0], r1 = d[0][2];
        if (t == 1) { r0 = d[1][0]; r1 = d[1][2]; }
        if (t == 2) { r0 = d[2][0]; r1 = d[2][2]; }
        if (t == 3) { r0 = d[3][0]; r1 = d[3][2]; }
        st_relaxed(a_out, make_uint4(__float_as_uint(r0), tag, __float_as_uint(r1), tag));
    }
    if (warp == 0) {
        final_reduce(&g_attn_part[((b * 32 + h) * NH + q4 * 8) * 8 + cp], tag, x0, x1, g0, g1,
                     reinterpret_cast<uint32_t*>(out + b * DM + h * 16), 1);
        if (lane == 0) { g_epoch[cta] = tag + 1; }
    }
}

}

extern "C" void kernel_launch(void* const* d_in, const int* in_sizes, int n_in, void* d_out, int out_size) {
    (void)in_sizes; (void)n_in; (void)out_size;
    const __nv_bfloat16* x  = (const __nv_bfloat16*)d_in[0];
    const __nv_bfloat16* Kc = (const __nv_bfloat16*)d_in[1];
    const __nv_bfloat16* Vc = (const __nv_bfloat16*)d_in[2];
    const __nv_bfloat16* wq = (const __nv_bfloat16*)d_in[3];
    const __nv_bfloat16* wo = (const __nv_bfloat16*)d_in[4];
    const __nv_bfloat16* w1 = (const __nv_bfloat16*)d_in[6];
    const __nv_bfloat16* w2 = (const __nv_bfloat16*)d_in[7];

    static bool attr_set = false;
    if (!attr_set) {
        cudaFuncSetAttribute(fk::fused_decode_kernel, cudaFuncAttributeMaxDynamicSharedMemorySize, fk::SMEM_BYTES);
        attr_set = true;
    }
    fk::fused_decode_kernel<<<fk::N_CTA, fk::NTHREADS, fk::SMEM_BYTES>>>(x, Kc, Vc, wq, wo, w1, w2, (__nv_bfloat16*)d_out);
}
```

```cpp
#include <cuda_runtime.h>
#include <cuda_bf16.h>
#include <stdint.h>

namespace fk {

#define FK_NST 4
#define FK_FIRST 2
#define FK_PRE 1
#define FK_INIT_AT 56
#define FK_WTILE 4
#define FK_WSTEP 10
#define FK_LEAD 0
#define FK_ENDT 16
#define FK_LEAD_END 48

constexpr int NB = 4, NH = 32, SK = 8192, DH = 128, DM = 512, FF = 1376;
constexpr int TK = 128;
constexpr int NT = SK / TK;
constexpr int STAGE_BYTES = TK * DH * 2;
constexpr int NST = FK_NST;
constexpr int NCW = 8;
constexpr int NTHREADS = NCW * 32;
constexpr int N_ATT = NB * NH;
constexpr int N_FFN = 4;
constexpr int FS = FF / N_FFN;
constexpr int N_CTA = N_ATT + N_FFN;
constexpr int NSEQ = 2 * NT;
static_assert(NST % 2 == 0, "K tiles live in the even stages, V tiles in the odd ones");

constexpr int OFF_W   = NST * STAGE_BYTES;
constexpr int OFF_XN  = OFF_W;
constexpr int OFF_X   = OFF_W + 8192;
constexpr int OFF_RED = OFF_W + 12288;
constexpr int OFF_BAR = OFF_W + STAGE_BYTES;
constexpr int OFF_Q   = OFF_BAR + 256;
constexpr int OFF_ML  = OFF_Q + 256;
constexpr int OFF_O   = OFF_ML + 64;
constexpr int SMEM_ATT = OFF_O + 256;
constexpr int FFN_CHUNK = 64 * FS * 2;
constexpr int NBF = (NST >= 6) ? 4 : 2;
constexpr int FFN_XN = NBF * FFN_CHUNK, FFN_H = FFN_XN + 8192, FFN_RED = FFN_H + 5504, FFN_BAR = FFN_RED + 32768;
constexpr int SMEM_FFN = FFN_BAR + 64;
static_assert(FFN_CHUNK == 43 * DM * 2, "chunk geometry");
constexpr int SMEM_BYTES = SMEM_ATT > SMEM_FFN ? SMEM_ATT : SMEM_FFN;

__device__ __align__(256) uint4 g_q_part[NH * NB * 32];
__device__ __align__(256) uint4 g_attn_part[NB * 32 * NH * 8];
__device__ __align__(256) uint4 g_ffn_part[NB * 32 * N_FFN * 8];
__device__ __align__(256) uint32_t g_progress[64];
#define FK_ONE4 1u, 1u, 1u, 1u
#define FK_ONE16 FK_ONE4, FK_ONE4, FK_ONE4, FK_ONE4
#define FK_ONE64 FK_ONE16, FK_ONE16, FK_ONE16, FK_ONE16
__device__ __align__(256) uint32_t g_epoch[N_CTA] = {FK_ONE64, FK_ONE64, FK_ONE4};

__device__ __forceinline__ uint32_t smem_u32(const void* p) { return (uint32_t)__cvta_generic_to_shared(p); }

__device__ __forceinline__ void mbar_init(uint32_t bar, uint32_t cnt) {
    asm volatile("mbarrier.init.shared::cta.b64 [%0], %1;" :: "r"(bar), "r"(cnt) : "memory");
}
__device__ __forceinline__ void mbar_expect_tx(uint32_t bar, uint32_t bytes) {
    asm volatile("mbarrier.arrive.expect_tx.shared::cta.b64 _, [%0], %1;" :: "r"(bar), "r"(bytes) : "memory");
}
__device__ __forceinline__ uint32_t atom_inc_shared(uint32_t addr) {
    uint32_t old;
    asm volatile("atom.relaxed.cta.shared::cta.add.u32 %0, [%1], 1;" : "=r"(old) : "r"(addr) : "memory");
    return old;
}
__device__ __forceinline__ void mbar_wait(uint32_t bar, uint32_t parity) {
    asm volatile(
        "{\n"
        ".reg .pred p;\n"
        "FK_WAIT:\n"
        "mbarrier.try_wait.parity.shared::cta.b64 p, [%0], %1;\n"
        "@p bra FK_DONE;\n"
        "bra FK_WAIT;\n"
        "FK_DONE:\n"
        "}\n" :: "r"(bar), "r"(parity) : "memory");
}
__device__ __forceinline__ void bulk_load(uint32_t dst, const void* src, uint32_t bytes, uint32_t bar, uint64_t pol) {
    asm volatile("cp.async.bulk.shared::cluster.global.mbarrier::complete_tx::bytes.L2::cache_hint [%0], [%1], %2, [%3], %4;"
                 :: "r"(dst), "l"(src), "r"(bytes), "r"(bar), "l"(pol) : "memory");
}
__device__ __forceinline__ uint4 ldg_nc(const void* p) {
    uint4 v;
    asm volatile("ld.global.nc.L1::no_allocate.v4.u32 {%0,%1,%2,%3}, [%4];"
                 : "=r"(v.x), "=r"(v.y), "=r"(v.z), "=r"(v.w) : "l"(p));
    return v;
}
__device__ __forceinline__ void bulk_load_plain(uint32_t dst, const void* src, uint32_t bytes, uint32_t bar) {
    asm volatile("cp.async.bulk.shared::cluster.global.mbarrier::complete_tx::bytes [%0], [%1], %2, [%3];"
                 :: "r"(dst), "l"(src), "r"(bytes), "r"(bar) : "memory");
}
__device__ __forceinline__ uint32_t ldg_nc32(const void* p) {
    uint32_t v;
    asm volatile("ld.global.nc.L1::no_allocate.u32 %0, [%1];" : "=r"(v) : "l"(p));
    return v;
}
__device__ __forceinline__ uint32_t lds32(uint32_t addr) {
    uint32_t v;
    asm volatile("ld.volatile.shared.u32 %0, [%1];" : "=r"(v) : "r"(addr) : "memory");
    return v;
}
__device__ __forceinline__ uint32_t pin(uint32_t v) {
    uint32_t r;
    asm volatile("mov.b32 %0, %1;" : "=r"(r) : "r"(v));
    return r;
}
__device__ __forceinline__ uint32_t ld_relaxed32(const uint32_t* p) {
    uint32_t v;
    asm volatile("ld.relaxed.gpu.global.u32 %0, [%1];" : "=r"(v) : "l"(p) : "memory");
    return v;
}
__device__ __forceinline__ bool mbar_test(uint32_t bar, uint32_t parity) {
    uint32_t ok;
    asm volatile("{\n.reg .pred p;\nmbarrier.test_wait.parity.shared::cta.b64 p, [%1], %2;\nselp.u32 %0, 1, 0, p;\n}\n"
                 : "=r"(ok) : "r"(bar), "r"(parity) : "memory");
    return ok != 0;
}
__device__ __forceinline__ uint4 ld_relaxed(const uint4* p) {
    uint4 v;
    asm volatile("ld.relaxed.gpu.global.v4.u32 {%0,%1,%2,%3}, [%4];"
                 : "=r"(v.x), "=r"(v.y), "=r"(v.z), "=r"(v.w) : "l"(p) : "memory");
    return v;
}
__device__ __forceinline__ void st_relaxed(uint4* p, uint4 v) {
    asm volatile("st.relaxed.gpu.global.v4.u32 [%0], {%1,%2,%3,%4};"
                 :: "l"(p), "r"(v.x), "r"(v.y), "r"(v.z), "r"(v.w) : "memory");
}
__device__ __forceinline__ void ldsm_x4(uint32_t (&r)[4], uint32_t addr) {
    asm volatile("ldmatrix.sync.aligned.m8n8.x4.shared.b16 {%0,%1,%2,%3}, [%4];"
                 : "=r"(r[0]), "=r"(r[1]), "=r"(r[2]), "=r"(r[3]) : "r"(addr) : "memory");
}
__device__ __forceinline__ void ldsm_x4_t(uint32_t (&r)[4], uint32_t addr) {
    asm volatile("ldmatrix.sync.aligned.m8n8.x4.trans.shared.b16 {%0,%1,%2,%3}, [%4];"
                 : "=r"(r[0]), "=r"(r[1]), "=r"(r[2]), "=r"(r[3]) : "r"(addr) : "memory");
}
__device__ __forceinline__ void mma_bf16(float (&c)[4], const uint32_t (&a)[4], uint32_t b0, uint32_t b1) {
    asm volatile("mma.sync.aligned.m16n8k16.row.col.f32.bf16.bf16.f32 {%0,%1,%2,%3}, {%4,%5,%6,%7}, {%8,%9}, {%0,%1,%2,%3};"
                 : "+f"(c[0]), "+f"(c[1]), "+f"(c[2]), "+f"(c[3])
                 : "r"(a[0]), "r"(a[1]), "r"(a[2]), "r"(a[3]), "r"(b0), "r"(b1));
}
__device__ __forceinline__ float ex2(float x) {
    float r;
    asm("ex2.approx.ftz.f32 %0, %1;" : "=f"(r) : "f"(x));
    return r;
}
__device__ __forceinline__ uint32_t pack_bf16(float lo, float hi) {
    uint32_t r;
    asm("cvt.rn.bf16x2.f32 %0, %1, %2;" : "=r"(r) : "f"(hi), "f"(lo));
    return r;
}
__device__ __forceinline__ float bf_lo(uint32_t w) { return __uint_as_float(w << 16); }
__device__ __forceinline__ float bf_hi(uint32_t w) { return __uint_as_float(w & 0xffff0000u); }
__device__ __forceinline__ float bf16r(float x) { return __bfloat162float(__float2bfloat16_rn(x)); }
__device__ __forceinline__ float silu_f(float x) { return x / (1.0f + __expf(-x)); }

__device__ __forceinline__ void warp_layernorm(const uint4 a, const uint4 b, float (&xn)[16]) {
    float v[16];
    v[0] = bf_lo(a.x); v[1] = bf_hi(a.x); v[2] = bf_lo(a.y); v[3] = bf_hi(a.y);
    v[4] = bf_lo(a.z); v[5] = bf_hi(a.z); v[6] = bf_lo(a.w); v[7] = bf_hi(a.w);
    v[8] = bf_lo(b.x); v[9] = bf_hi(b.x); v[10] = bf_lo(b.y); v[11] = bf_hi(b.y);
    v[12] = bf_lo(b.z); v[13] = bf_hi(b.z); v[14] = bf_lo(b.w); v[15] = bf_hi(b.w);
    float s = 0.f;
#pragma unroll
    for (int i = 0; i < 16; i++) s += v[i];
#pragma unroll
    for (int o = 16; o; o >>= 1) s += __shfl_xor_sync(0xffffffffu, s, o);
    const float mean = s * (1.0f / DM);
    float ss = 0.f;
#pragma unroll
    for (int i = 0; i < 16; i++) { const float d = v[i] - mean; ss = fmaf(d, d, ss); }
#pragma unroll
    for (int o = 16; o; o >>= 1) ss += __shfl_xor_sync(0xffffffffu, ss, o);
    const float m_bf = bf16r(mean);
    const float den = bf16r(sqrtf(bf16r(bf16r(ss * (1.0f / DM)) + 1e-5f)));
#pragma unroll
    for (int i = 0; i < 16; i++) xn[i] = bf16r(__fdiv_rn(bf16r(v[i] - m_bf), den));
}

__device__ __forceinline__ bool ll_valid(const uint4& v, uint32_t tag) { return v.y == tag && v.w == tag; }

__device__ __forceinline__ void ffn_cta(uint8_t* smem, int f, uint32_t tag,
                                        const __nv_bfloat16* __restrict__ x,
                                        const __nv_bfloat16* __restrict__ w1,
                                        const __nv_bfloat16* __restrict__ w2) {
    const int tid = threadIdx.x, warp = tid >> 5, lane = tid & 31;
    const uint32_t sbase = smem_u32(smem), bar = sbase + FFN_BAR;
    float* xnT = reinterpret_cast<float*>(smem + FFN_XN);
    float* hT  = reinterpret_cast<float*>(smem + FFN_H);
    float* red = reinterpret_cast<float*>(smem + FFN_RED);
    if (tid == 0) {
#pragma unroll
        for (int s = 0; s < NBF; s++) mbar_init(bar + s * 8, 1);
    }
    __syncthreads();
    auto issue = [&](int c) {
        const int s = c % NBF;
        if (tid == 0) mbar_expect_tx(bar + s * 8, FFN_CHUNK);
        if (c < 8) {
            __syncthreads();
            if (tid < 64) bulk_load_plain(sbase + s * FFN_CHUNK + tid * (FS * 2), w1 + (size_t)(c * 64 + tid) * FF + f * FS, FS * 2, bar + s * 8);
        } else if (tid == 0) {
            bulk_load_plain(sbase + s * FFN_CHUNK, w2 + (size_t)(f * FS + (c - 8) * 43) * DM, FFN_CHUNK, bar + s * 8);
        }
    };
    for (int c = 0; c < NBF; c++) issue(c);
    if (warp < NB) {
        float xn[16];
        const uint4 xa = ldg_nc(x + warp * DM + lane * 16), xb = ldg_nc(x + warp * DM + lane * 16 + 8);
        warp_layernorm(xa, xb, xn);
#pragma unroll
        for (int i = 0; i < 16; i++) xnT[(lane * 16 + i) * 4 + warp] = xn[i];
    }
    __syncthreads();
    float acc[4][8];
#pragma unroll
    for (int b = 0; b < 4; b++)
#pragma unroll
        for (int c = 0; c < 8; c++) acc[b][c] = 0.f;
#pragma unroll 1
    for (int c = 0; c < 16; c++) {
        const int s = c % NBF;
        mbar_wait(bar + s * 8, (c / NBF) & 1);
        const bool st1 = c < 8;
        const int cg = st1 ? tid % 43 : (tid & 63), r0 = st1 ? tid / 43 : (tid >> 6);
        const int rstep = st1 ? 5 : 4, nrows = st1 ? 64 : 43, rbytes = st1 ? FS * 2 : DM * 2;
        const float* vec = st1 ? xnT + c * 64 * 4 : hT + (c - 8) * 43 * 4;
        const uint8_t* wb = smem + s * FFN_CHUNK + cg * 16;
        if (!st1 || tid < 43 * 5) {
#pragma unroll 2
            for (int k = r0; k < nrows; k += rstep) {
                const uint4 w = *reinterpret_cast<const uint4*>(wb + k * rbytes);
                const float4 xv = *reinterpret_cast<const float4*>(vec + k * 4);
                const float wf[8] = {bf_lo(w.x), bf_hi(w.x), bf_lo(w.y), bf_hi(w.y), bf_lo(w.z), bf_hi(w.z), bf_lo(w.w), bf_hi(w.w)};
#pragma unroll
                for (int j = 0; j < 8; j++) {
                    acc[0][j] = fmaf(xv.x, wf[j], acc[0][j]);
                    acc[1][j] = fmaf(xv.y, wf[j], acc[1][j]);
                    acc[2][j] = fmaf(xv.z, wf[j], acc[2][j]);
                    acc[3][j] = fmaf(xv.w, wf[j], acc[3][j]);
                }
            }
        }
        __syncthreads();
        if (c + NBF < 16) issue(c + NBF);
        if (c == 7) {
            if (tid < 43 * 5) {
#pragma unroll
                for (int b = 0; b < 4; b++)
#pragma unroll
                    for (int j = 0; j < 8; j++) red[(r0 * 4 + b) * FS + cg * 8 + j] = acc[b][j];
            }
#pragma unroll
            for (int b = 0; b < 4; b++)
#pragma unroll
                for (int j = 0; j < 8; j++) acc[b][j] = 0.f;
            __syncthreads();
            for (int i = tid; i < 4 * FS; i += NTHREADS) {
                const int b = i / FS, cc = i % FS;
                float sum = 0.f;
#pragma unroll
                for (int ks = 0; ks < 5; ks++) sum += red[(ks * 4 + b) * FS + cc];
                hT[cc * 4 + b] = bf16r(silu_f(bf16r(sum)));
            }
            __syncthreads();
        }
    }
    {
        const int cg = tid & 63, fs = tid >> 6;
#pragma unroll
        for (int b = 0; b < 4; b++)
#pragma unroll
            for (int j = 0; j < 8; j++) red[(fs * 4 + b) * DM + cg * 8 + j] = acc[b][j];
    }
    __syncthreads();
    for (int i = tid; i < NB * 256; i += NTHREADS) {
        const int b = i >> 8, j = (i >> 3) & 31, p = i & 7;
        float s0 = 0.f, s1 = 0.f;
#pragma unroll
        for (int fs = 0; fs < 4; fs++) { s0 += red[(fs * 4 + b) * DM + 16 * j + p]; s1 += red[(fs * 4 + b) * DM + 16 * j + 8 + p]; }
        st_relaxed(&g_ffn_part[((b * 32 + j) * N_FFN + f) * 8 + p],
                   make_uint4(__float_as_uint(s0), tag, __float_as_uint(s1), tag));
    }
}

__global__ void __launch_bounds__(NTHREADS, 1)
fused_decode_kernel(const __nv_bfloat16* __restrict__ x, const __nv_bfloat16* __restrict__ Kc,
                    const __nv_bfloat16* __restrict__ Vc, const __nv_bfloat16* __restrict__ wq,
                    const __nv_bfloat16* __restrict__ wo, const __nv_bfloat16* __restrict__ w1,
                    const __nv_bfloat16* __restrict__ w2, __nv_bfloat16* __restrict__ out) {
    extern __shared__ __align__(1024) uint8_t smem[];
    const int cta = blockIdx.x;
    const int tid = threadIdx.x, warp = tid >> 5, lane = tid & 31;
    if (cta >= N_ATT) {
        const uint32_t tag = ld_relaxed32(&g_epoch[cta]);
        ffn_cta(smem, cta - N_ATT, tag, x, w1, w2);
        if (tid == 0) { g_epoch[cta] = tag + 1; }
        return;
    }

    const int b = cta & 3, h = cta >> 2;
    const int bh = b * NH + h;
    const uint32_t sbase = pin(smem_u32(smem));
    const uint32_t bar_full = sbase + OFF_BAR;
    const uint32_t cnt_rel = bar_full + NST * 8;
    const char* kp = reinterpret_cast<const char*>(Kc) + (size_t)bh * SK * DH * 2;
    const char* vp = reinterpret_cast<const char*>(Vc) + (size_t)bh * SK * DH * 2;
    const char* wop = reinterpret_cast<const char*>(wo) + (size_t)h * DH * DM * 2;
    uint64_t pol;
    asm volatile("createpolicy.fractional.L2::evict_first.b64 %0, 1.0;" : "=l"(pol));
    auto issue_kv = [&](const char* src, int s) {
        const uint32_t bar = bar_full + s * 8;
        mbar_expect_tx(bar, STAGE_BYTES);
        bulk_load(sbase + s * STAGE_BYTES, src, STAGE_BYTES, bar, pol);
    };
    auto issue_first = [&](int n) { issue_kv(((n & 1) ? vp : kp) + (size_t)(n >> 1) * STAGE_BYTES, n); };
    const uint32_t bar_w = bar_full + 216, cnt_w = bar_full + 224;
    auto issue_w = [&](int q) {
        mbar_expect_tx(bar_w, STAGE_BYTES);
        bulk_load_plain(sbase + OFF_W, wop + (size_t)q * STAGE_BYTES, STAGE_BYTES, bar_w);
    };

    const int g = lane >> 2, t = lane & 3;
    float* xn_s  = reinterpret_cast<float*>(smem + OFF_XN);
    float* red_s = reinterpret_cast<float*>(smem + OFF_RED);
    __nv_bfloat16* q_s = reinterpret_cast<__nv_bfloat16*>(smem + OFF_Q);
    float* ml_s = reinterpret_cast<float*>(smem + OFF_ML);
    __nv_bfloat16* o_s = reinterpret_cast<__nv_bfloat16*>(smem + OFF_O);

    uint4* const q_out = &g_q_part[(h * NB + (lane >> 3)) * 32 + b * 8 + (lane & 7)];
    uint4* const a_out = &g_attn_part[((b * 32 + warp * 4 + t) * NH + h) * 8 + g];

    volatile uint32_t* q_flag = reinterpret_cast<volatile uint32_t*>(smem + OFF_BAR + 192);
    const uint32_t bar_x = bar_full + 200;
    if (tid == 0) {
        mbar_init(bar_full, 1);
        issue_first(0);
        mbar_init(bar_x, 1);
        mbar_expect_tx(bar_x, NB * DM * 2);
        bulk_load_plain(sbase + OFF_X, x, NB * DM * 2, bar_x);
#pragma unroll
        for (int s = 1; s < NST; s++) mbar_init(bar_full + s * 8, 1);
        mbar_init(bar_w, 1);
#pragma unroll
        for (int s = 0; s < NST; s++) *reinterpret_cast<volatile uint32_t*>(smem + OFF_BAR + NST * 8 + s * 4) = 0;
        *reinterpret_cast<volatile uint32_t*>(smem + OFF_BAR + 224) = 0;
        *q_flag = 0;
#pragma unroll 1
        for (int s = 1; s < FK_PRE; s++) issue_first(s);
    }
    uint32_t qf[8][2];
    uint32_t tag;
    {
        uint32_t w[32];
        const __nv_bfloat16* wp = wq + (size_t)(warp * 64 + (lane >> 4) * 32) * (NH * DH) + h * DH + b * 32 + (lane & 15) * 2;
#pragma unroll
        for (int i = 0; i < 32; i++) w[i] = ldg_nc32(wp + (size_t)i * (NH * DH));
        tag = ld_relaxed32(&g_epoch[cta]);
        if (tid == 0) {
#pragma unroll 1
            for (int s = FK_PRE; s < FK_FIRST; s++) issue_first(s);
            asm volatile("prefetch.global.L2 [%0];" :: "l"(wop));
        }
        if (warp == 0) st_relaxed(q_out, make_uint4(0, 0, 0, 0));
        if (FK_INIT_AT < 0) st_relaxed(a_out, make_uint4(0, 0, 0, 0));
        __syncthreads();
        if (warp < 4) {
            float xn[16];
            mbar_wait(bar_x, 0);
            const uint4 xa = *reinterpret_cast<const uint4*>(smem + OFF_X + warp * DM * 2 + lane * 32);
            const uint4 xb = *reinterpret_cast<const uint4*>(smem + OFF_X + warp * DM * 2 + lane * 32 + 16);
            warp_layernorm(xa, xb, xn);
#pragma unroll
            for (int i = 0; i < 16; i += 4)
                *reinterpret_cast<float4*>(xn_s + warp * DM + lane * 16 + i) = make_float4(xn[i], xn[i + 1], xn[i + 2], xn[i + 3]);
        }
        __syncthreads();
        float acc[4][2];
#pragma unroll
        for (int bb = 0; bb < 4; bb++) acc[bb][0] = acc[bb][1] = 0.f;
        const float* xp = xn_s + warp * 64 + (lane >> 4) * 32;
#pragma unroll
        for (int i4 = 0; i4 < 8; i4++) {
#pragma unroll
            for (int bb = 0; bb < 4; bb++) {
                const float4 xv = *reinterpret_cast<const float4*>(xp + bb * DM + i4 * 4);
                const float xs[4] = {xv.x, xv.y, xv.z, xv.w};
#pragma unroll
                for (int u = 0; u < 4; u++) {
                    acc[bb][0] = fmaf(xs[u], bf_lo(w[i4 * 4 + u]), acc[bb][0]);
                    acc[bb][1] = fmaf(xs[u], bf_hi(w[i4 * 4 + u]), acc[bb][1]);
                }
            }
        }
        const bool up = lane >= 16;
        float k0 = up ? acc[2][0] : acc[0][0], k1 = up ? acc[2][1] : acc[0][1];
        float k2 = up ? acc[3][0] : acc[1][0], k3 = up ? acc[3][1] : acc[1][1];
        k0 += __shfl_xor_sync(0xffffffffu, up ? acc[0][0] : acc[2][0], 16);
        k1 += __shfl_xor_sync(0xffffffffu, up ? acc[0][1] : acc[2][1], 16);
        k2 += __shfl_xor_sync(0xffffffffu, up ? acc[1][0] : acc[3][0], 16);
        k3 += __shfl_xor_sync(0xffffffffu, up ? acc[1][1] : acc[3][1], 16);
        float* rp = red_s + warp * 128 + (up ? 64 : 0) + (lane & 15) * 2;
        *reinterpret_cast<float2*>(rp)      = make_float2(k0, k1);
        *reinterpret_cast<float2*>(rp + 32) = make_float2(k2, k3);
        __syncthreads();
        if (warp == 0) {
            float4 s = make_float4(0.f, 0.f, 0.f, 0.f);
#pragma unroll
            for (int w8 = 0; w8 < NCW; w8++) {
                const float4 v = *reinterpret_cast<const float4*>(red_s + w8 * 128 + lane * 4);
                s.x += v.x; s.y += v.y; s.z += v.z; s.w += v.w;
            }
            st_relaxed(q_out, make_uint4(pack_bf16(s.x, s.y), tag, pack_bf16(s.z, s.w), tag));
            const uint4* p = &g_q_part[(h * NB + b) * 32 + lane];
            uint4 v = ld_relaxed(p);
            for (int spin = 0; !ll_valid(v, tag) && spin < (1 << 20); spin++) v = ld_relaxed(p);
            *reinterpret_cast<uint2*>(q_s + lane * 4) = make_uint2(v.x, v.z);
            if (lane == 0) *q_flag = 1;
        }
        if (tid == NTHREADS - 32) {
            int next = FK_FIRST, watch = 0;
            while (next < NST) {
                if (mbar_test(bar_full + watch * 8, 0)) { issue_first(next); next++; watch++; }
                else if (*q_flag) break;
            }
#pragma unroll 1
            for (; next < NST; next++) issue_first(next);
        }
        __syncthreads();
#pragma unroll
        for (int j = 0; j < 8; j++) {
            const int c = (j ^ g) & 7;
            qf[j][0] = *reinterpret_cast<const uint32_t*>(q_s + c * 8 + 2 * t);
            qf[j][1] = *reinterpret_cast<const uint32_t*>(q_s + 64 + c * 8 + 2 * t);
        }
    }

    constexpr float RSQRT_DH = 0.08838834764831845f, LOG2E = 1.4426950408889634f;
    const int li = lane & 7, lm = lane >> 3;
    const uint32_t k_base = pin(sbase + (uint32_t)((warp * 16 + li + 8 * (lm & 1)) * 256 + (lm >> 1) * 128 + li * 16));
    const uint32_t v_base = pin(sbase + (uint32_t)((warp * 16 + li + 8 * (lm >> 1)) * 256 + (lm & 1) * 128 + li * 16));
    const bool diag = (t == (g >> 1));
    uint32_t msk[8];
#pragma unroll
    for (int j = 0; j < 8; j++) msk[j] = pin((j == (g ^ (2 * t)) ? 0x0000ffffu : 0u) | (j == (g ^ (2 * t) ^ 1) ? 0xffff0000u : 0u));
    const uint32_t ones[4] = {0x3f803f80u, 0x3f803f80u, 0x3f803f80u, 0x3f803f80u};

    float acc0[4] = {0.f, 0.f, 0.f, 0.f}, acc1[4] = {0.f, 0.f, 0.f, 0.f}, lacc[4] = {0.f, 0.f, 0.f, 0.f};
    float m_raw = -INFINITY;
    float m_run = -INFINITY, mc = 0.f;
    float fin_scale = 0.f;
    int st = 0; uint32_t ph = 0;
    int seq = NST;
    uint32_t wa[8][4][4];
    float g0 = 0.f, g1 = 0.f;
    uint4 gv = make_uint4(0, 0, 0, 0);
    const int cp = lane & 7, q4 = lane >> 3;
    const float x0 = __bfloat162float(reinterpret_cast<const __nv_bfloat16*>(smem + OFF_X)[b * DM + h * 16 + cp]);
    const float x1 = __bfloat162float(reinterpret_cast<const __nv_bfloat16*>(smem + OFF_X)[b * DM + h * 16 + 8 + cp]);
    const uint32_t prog_base = (tag - 1) * (uint32_t)(N_ATT * NT);
    const uint32_t prog_s = bar_full + 208;
    uint32_t prog_v = prog_base;
    if (tid == 0) *reinterpret_cast<volatile uint32_t*>(smem + OFF_BAR + 208) = prog_base;
    __syncthreads();
    auto pace = [&](uint32_t pv, uint32_t lim) {
        for (int spin = 0; (int)(pv - lim) < 0 && spin < 4096; spin++) pv = ld_relaxed32(&g_progress[0]);
    };

#pragma unroll 1
    for (int it = 0; it < NT; it++) {
#pragma unroll
        for (int q = 0; q <= 4; q++) {
            if (it == FK_WTILE + q * FK_WSTEP) {
                if (q == 0) {
                    if (tid == 0) {
                        asm volatile("fence.proxy.async.shared::cta;" ::: "memory");
                        issue_w(0);
                    }
                } else {
                    mbar_wait(bar_w, (q - 1) & 1);
                    const uint32_t wb = sbase + OFF_W + (li + 8 * (lane >> 4)) * 1024 + warp * 128 + (lm & 1) * 16;
#pragma unroll
                    for (int j = 0; j < 4; j++) {
                        ldsm_x4_t(wa[2 * q - 2][j], wb + j * 32);
                        ldsm_x4_t(wa[2 * q - 1][j], wb + 16384 + j * 32);
                    }
                    if (q < 4 && lane == 0) {
                        const uint32_t rel = atom_inc_shared(cnt_w);
                        if ((rel & (NCW - 1)) == NCW - 1) issue_w(q);
                    }
                }
                __syncwarp();
            }
        }
        if (it == FK_INIT_AT) st_relaxed(a_out, make_uint4(0, 0, 0, 0));
        if (it == NT - 12 && warp == 0) {
            gv = ld_relaxed(&g_ffn_part[((b * 32 + h) * N_FFN + q4) * 8 + cp]);
        }
        if (it == NT - 2 && warp == 0) {
            const uint4* p = &g_ffn_part[((b * 32 + h) * N_FFN + q4) * 8 + cp];
            uint4 v = gv;
            for (int spin = 0; !ll_valid(v, tag) && spin < (1 << 20); spin++) { __nanosleep(64); v = ld_relaxed(p); }
            __syncwarp();
            g0 = __uint_as_float(v.x); g1 = __uint_as_float(v.z);
            g0 += __shfl_xor_sync(0xffffffffu, g0, 8);  g1 += __shfl_xor_sync(0xffffffffu, g1, 8);
            g0 += __shfl_xor_sync(0xffffffffu, g0, 16); g1 += __shfl_xor_sync(0xffffffffu, g1, 16);
            g0 = bf16r(silu_f(bf16r(g0))); g1 = bf16r(silu_f(bf16r(g1)));
        }
        if (tid == 0) {
            *reinterpret_cast<volatile uint32_t*>(smem + OFF_BAR + 208) = prog_v;
            prog_v = ld_relaxed32(&g_progress[0]);
        }
        const bool endgame = it >= NT - FK_ENDT;
        const char* k_next = kp + (size_t)(it + NST / 2) * STAGE_BYTES;
        const char* v_next = vp + (size_t)(it + NST / 2) * STAGE_BYTES;
        mbar_wait(bar_full + st * 8, ph);
        float c0[4] = {0.f, 0.f, 0.f, 0.f}, c1[4] = {0.f, 0.f, 0.f, 0.f};
        uint32_t relK = 0, pvK = 0;
        const uint32_t kb = k_base + st * STAGE_BYTES;
        {
#pragma unroll
            for (int j = 0; j < 8; j++) {
                uint32_t a[4];
                ldsm_x4(a, kb ^ (j << 4));
                mma_bf16((j & 1) ? c1 : c0, a, qf[j][0], qf[j][1]);
            }
            if (!endgame && seq < NSEQ && lane == 0) {
                relK = atom_inc_shared(cnt_rel + st * 4);
                pvK = lds32(prog_s);
            }
        }
        const float u0 = (g & 1) ? (c0[1] + c1[1]) : (c0[0] + c1[0]);
        const float u1 = (g & 1) ? (c0[3] + c1[3]) : (c0[2] + c1[2]);
        int key = __float_as_int(diag ? fmaxf(u0, u1) : -INFINITY);
        key ^= (key >> 31) & 0x7fffffff;
        key = __reduce_max_sync(0xffffffffu, key);
        const uint32_t r1 = pack_bf16(u0, u1);
        const uint32_t r2 = pack_bf16(bf_lo(r1) * RSQRT_DH, bf_hi(r1) * RSQRT_DH);
        const float s0 = diag ? bf_lo(r2) : -INFINITY, s1 = diag ? bf_hi(r2) : -INFINITY;
        key ^= (key >> 31) & 0x7fffffff;
        const float tmax = __int_as_float(key);
        if (tmax > m_raw) {
            m_raw = tmax;
            const float m_new = bf16r(bf16r(tmax) * RSQRT_DH);
            const float sc = ex2((m_run - m_new) * LOG2E);
#pragma unroll
            for (int i = 0; i < 4; i++) { acc0[i] *= sc; acc1[i] *= sc; }
            lacc[0] *= sc;
            m_run = m_new;
            mc = -m_new * LOG2E;
        }
        const uint32_t pk = pack_bf16(ex2(fmaf(s0, LOG2E, mc)), ex2(fmaf(s1, LOG2E, mc)));
        const uint32_t xx = __shfl_sync(0xffffffffu, pk, 9 * t), yy = __shfl_sync(0xffffffffu, pk, 9 * t + 4);
        const uint32_t pp0 = __byte_perm(xx, yy, 0x5410), pp1 = __byte_perm(xx, yy, 0x7632);
        if ((relK & (NCW - 1)) == NCW - 1) {
            pace(pvK, prog_base + (uint32_t)(it * N_ATT - (FK_LEAD)));
            issue_kv(k_next, st);
        }
        __syncwarp();
        const int stK = st;
        seq++;
        if (++st == NST) { st = 0; ph ^= 1; }
        mma_bf16(lacc, ones, pp0, pp1);
        if (it == NT - 1) {
            if (lane == 0) { ml_s[warp] = m_run; ml_s[8 + warp] = lacc[0]; }
            __syncthreads();
            const float4 ma = *reinterpret_cast<const float4*>(ml_s), mb = *reinterpret_cast<const float4*>(ml_s + 4);
            const float4 la = *reinterpret_cast<const float4*>(ml_s + 8), lb = *reinterpret_cast<const float4*>(ml_s + 12);
            const float M = fmaxf(fmaxf(fmaxf(ma.x, ma.y), fmaxf(ma.z, ma.w)), fmaxf(fmaxf(mb.x, mb.y), fmaxf(mb.z, mb.w)));
            const float L = (ex2((ma.x - M) * LOG2E) * la.x + ex2((ma.y - M) * LOG2E) * la.y) + (ex2((ma.z - M) * LOG2E) * la.z + ex2((ma.w - M) * LOG2E) * la.w)
                          + (ex2((mb.x - M) * LOG2E) * lb.x + ex2((mb.y - M) * LOG2E) * lb.y) + (ex2((mb.z - M) * LOG2E) * lb.z + ex2((mb.w - M) * LOG2E) * lb.w);
            fin_scale = __fdividef(ex2((m_run - M) * LOG2E), L);
        }
        mbar_wait(bar_full + st * 8, ph);
        const uint32_t vb = v_base + st * STAGE_BYTES;
        {
            uint32_t relV = 0, pvV = 0;
#pragma unroll
            for (int j = 0; j < 8; j++) {
                uint32_t a[4];
                ldsm_x4_t(a, vb ^ (j << 4));
                mma_bf16((j & 1) ? acc1 : acc0, a, pp0 & msk[j], pp1 & msk[j]);
            }
            if (seq - (endgame ? 1 : 0) < NSEQ && lane == 0) {
                relV = atom_inc_shared(cnt_rel + st * 4);
                pvV = lds32(prog_s);
            }
            if (tid == NTHREADS - 32) asm volatile("red.relaxed.gpu.global.add.u32 [%0], 1;" :: "l"(&g_progress[0]) : "memory");
            if ((relV & (NCW - 1)) == NCW - 1) {
                if (endgame) {
                    pace(pvV, prog_base + (uint32_t)((it + 1) * N_ATT - (FK_LEAD_END)));
                    issue_kv(k_next, stK);
                }
                if (seq < NSEQ) issue_kv(v_next, st);
            }
        }
        __syncwarp();
        seq++;
        if (++st == NST) { st = 0; ph ^= 1; }
    }

    if ((prog_v ^ gv.x ^ gv.y ^ gv.z ^ gv.w) == 0x9e3779b9u) *reinterpret_cast<volatile uint32_t*>(smem + OFF_BAR + 240) = 0;
    const uint4* inbox = &g_attn_part[((b * 32 + h) * NH + q4 * 8) * 8 + cp];
    asm volatile("" : "+l"(inbox));
    {
        float* o = red_s + warp * 128;
        o[16 * t + g]          = (acc0[0] + acc1[0]) * fin_scale;
        o[16 * t + 8 + g]      = (acc0[1] + acc1[1]) * fin_scale;
        o[64 + 16 * t + g]     = (acc0[2] + acc1[2]) * fin_scale;
        o[64 + 16 * t + 8 + g] = (acc0[3] + acc1[3]) * fin_scale;
    }
    __syncthreads();
    if (tid < DH) {
        float v[8];
#pragma unroll
        for (int w = 0; w < 8; w++) v[w] = red_s[w * 128 + tid];
        const float o = ((v[0] + v[1]) + (v[2] + v[3])) + ((v[4] + v[5]) + (v[6] + v[7]));
        o_s[((tid >> 1) & 3) * 32 + (tid >> 4) * 4 + ((tid >> 3) & 1) * 2 + (tid & 1)] = __float2bfloat16_rn(o);
    }
    __syncthreads();
    {
        float d[4][4];
#pragma unroll
        for (int j = 0; j < 4; j++) { d[j][0] = d[j][1] = d[j][2] = d[j][3] = 0.f; }
        uint4 ov[4];
#pragma unroll
        for (int i = 0; i < 4; i++) ov[i] = *reinterpret_cast<const uint4*>(o_s + t * 32 + i * 8);
#pragma unroll
        for (int i = 0; i < 4; i++) {
#pragma unroll
            for (int j = 0; j < 4; j++) mma_bf16(d[j], wa[2 * i][j], ov[i].x, ov[i].y);
#pragma unroll
            for (int j = 0; j < 4; j++) mma_bf16(d[j], wa[2 * i + 1][j], ov[i].z, ov[i].w);
        }
        float r0 = d[0][0], r1 = d[0][2];
        if (t == 1) { r0 = d[1][0]; r1 = d[1][2]; }
        if (t == 2) { r0 = d[2][0]; r1 = d[2][2]; }
        if (t == 3) { r0 = d[3][0]; r1 = d[3][2]; }
        st_relaxed(a_out, make_uint4(__float_as_uint(r0), tag, __float_as_uint(r1), tag));
    }
    if (warp == 0) {
        const uint4* p = inbox;
        uint4 v[8];
#pragma unroll
        for (int i = 0; i < 8; i++) v[i] = ld_relaxed(p + i * 8);
        for (int spin = 0; spin < (1 << 20); spin++) {
            bool ok = true;
#pragma unroll
            for (int i = 0; i < 8; i++) {
                if (!ll_valid(v[i], tag)) { v[i] = ld_relaxed(p + i * 8); ok = false; }
            }
            if (ok) break;
        }
        __syncwarp();
        float s0 = ((__uint_as_float(v[0].x) + __uint_as_float(v[1].x)) + (__uint_as_float(v[2].x) + __uint_as_float(v[3].x)))
                 + ((__uint_as_float(v[4].x) + __uint_as_float(v[5].x)) + (__uint_as_float(v[6].x) + __uint_as_float(v[7].x)));
        float s1 = ((__uint_as_float(v[0].z) + __uint_as_float(v[1].z)) + (__uint_as_float(v[2].z) + __uint_as_float(v[3].z)))
                 + ((__uint_as_float(v[4].z) + __uint_as_float(v[5].z)) + (__uint_as_float(v[6].z) + __uint_as_float(v[7].z)));
        s0 += __shfl_xor_sync(0xffffffffu, s0, 8);  s1 += __shfl_xor_sync(0xffffffffu, s1, 8);
        s0 += __shfl_xor_sync(0xffffffffu, s0, 16); s1 += __shfl_xor_sync(0xffffffffu, s1, 16);
        const uint32_t sb = pack_bf16(s0, s1);
        const uint32_t sg = pack_bf16(bf_lo(sb) * g0, bf_hi(sb) * g1);
        const uint32_t ob = pack_bf16(x0 + bf_lo(sg), x1 + bf_hi(sg));
        const int src = (2 * lane) & 7;
        const uint32_t e0 = __shfl_sync(0xffffffffu, ob, src), e1 = __shfl_sync(0xffffffffu, ob, src + 1);
        if (lane < 8)
            *reinterpret_cast<uint32_t*>(out + b * DM + h * 16 + 2 * lane) = __byte_perm(e0, e1, lane < 4 ? 0x5410 : 0x7632);
        if (lane == 0) { g_epoch[cta] = tag + 1; }
    }
}

}

extern "C" void kernel_launch(void* const* d_in, const int* in_sizes, int n_in, void* d_out, int out_size) {
    (void)in_sizes; (void)n_in; (void)out_size;
    const __nv_bfloat16* x  = (const __nv_bfloat16*)d_in[0];
    const __nv_bfloat16* Kc = (const __nv_bfloat16*)d_in[1];
    const __nv_bfloat16* Vc = (const __nv_bfloat16*)d_in[2];
    const __nv_bfloat16* wq = (const __nv_bfloat16*)d_in[3];
    const __nv_bfloat16* wo = (const __nv_bfloat16*)d_in[4];
    const __nv_bfloat16* w1 = (const __nv_bfloat16*)d_in[6];
    const __nv_bfloat16* w2 = (const __nv_bfloat16*)d_in[7];

    static bool attr_set = false;
    if (!attr_set) {
        cudaFuncSetAttribute(fk::fused_decode_kernel, cudaFuncAttributeMaxDynamicSharedMemorySize, fk::SMEM_BYTES);
        attr_set = true;
    }
    fk::fused_decode_kernel<<<fk::N_CTA, fk::NTHREADS, fk::SMEM_BYTES>>>(x, Kc, Vc, wq, wo, w1, w2, (__nv_bfloat16*)d_out);
}
```

```cpp
#include <cuda_runtime.h>
#include <cuda_bf16.h>
#include <stdint.h>

namespace fk {

#define FK_NST 4
#define FK_FIRST 2
#define FK_PRE 1
#define FK_INIT_AT 56
#define FK_WTILE 4
#define FK_WSTEP 10
#define FK_LEAD 0
#define FK_ENDT 16
#define FK_LEAD_END 48

constexpr int NB = 4, NH = 32, SK = 8192, DH = 128, DM = 512, FF = 1376;
constexpr int TK = 128;
constexpr int NT = SK / TK;
constexpr int STAGE_BYTES = TK * DH * 2;
constexpr int NST = FK_NST;
constexpr int NCW = 8;
constexpr int NTHREADS = NCW * 32;
constexpr int N_ATT = NB * NH;
constexpr int N_FFN = 4;
constexpr int FS = FF / N_FFN;
constexpr int N_CTA = N_ATT + N_FFN;
constexpr int NSEQ = 2 * NT;
static_assert(NST % 2 == 0, "K tiles live in the even stages, V tiles in the odd ones");

constexpr int OFF_W   = NST * STAGE_BYTES;
constexpr int OFF_XN  = OFF_W;
constexpr int OFF_X   = OFF_W + 8192;
constexpr int OFF_RED = OFF_W + 12288;
constexpr int OFF_BAR = OFF_W + STAGE_BYTES;
constexpr int OFF_Q   = OFF_BAR + 256;
constexpr int OFF_ML  = OFF_Q + 256;
constexpr int OFF_O   = OFF_ML + 64;
constexpr int SMEM_ATT = OFF_O + 256;
constexpr int FFN_CHUNK = 64 * FS * 2;
constexpr int NBF = (NST >= 6) ? 4 : 2;
constexpr int FFN_XN = NBF * FFN_CHUNK, FFN_H = FFN_XN + 8192, FFN_RED = FFN_H + 5504, FFN_BAR = FFN_RED + 32768;
constexpr int SMEM_FFN = FFN_BAR + 64;
static_assert(FFN_CHUNK == 43 * DM * 2, "chunk geometry");
constexpr int SMEM_BYTES = SMEM_ATT > SMEM_FFN ? SMEM_ATT : SMEM_FFN;

__device__ __align__(256) uint4 g_q_part[NH * NB * 32];
__device__ __align__(256) uint4 g_attn_part[NB * 32 * NH * 8];
__device__ __align__(256) uint4 g_ffn_part[NB * 32 * N_FFN * 8];
__device__ __align__(256) uint32_t g_progress[64];
#define FK_ONE4 1u, 1u, 1u, 1u
#define FK_ONE16 FK_ONE4, FK_ONE4, FK_ONE4, FK_ONE4
#define FK_ONE64 FK_ONE16, FK_ONE16, FK_ONE16, FK_ONE16
__device__ __align__(256) uint32_t g_epoch[N_CTA] = {FK_ONE64, FK_ONE64, FK_ONE4};

__device__ __forceinline__ uint32_t smem_u32(const void* p) { return (uint32_t)__cvta_generic_to_shared(p); }

__device__ __forceinline__ void mbar_init(uint32_t bar, uint32_t cnt) {
    asm volatile("mbarrier.init.shared::cta.b64 [%0], %1;" :: "r"(bar), "r"(cnt) : "memory");
}
__device__ __forceinline__ void mbar_expect_tx(uint32_t bar, uint32_t bytes) {
    asm volatile("mbarrier.arrive.expect_tx.shared::cta.b64 _, [%0], %1;" :: "r"(bar), "r"(bytes) : "memory");
}
__device__ __forceinline__ uint32_t atom_inc_shared(uint32_t addr) {
    uint32_t old;
    asm volatile("atom.relaxed.cta.shared::cta.add.u32 %0, [%1], 1;" : "=r"(old) : "r"(addr) : "memory");
    return old;
}
__device__ __forceinline__ void mbar_wait(uint32_t bar, uint32_t parity) {
    asm volatile(
        "{\n"
        ".reg .pred p;\n"
        "FK_WAIT:\n"
        "mbarrier.try_wait.parity.shared::cta.b64 p, [%0], %1;\n"
        "@p bra FK_DONE;\n"
        "bra FK_WAIT;\n"
        "FK_DONE:\n"
        "}\n" :: "r"(bar), "r"(parity) : "memory");
}
__device__ __forceinline__ void bulk_load(uint32_t dst, const void* src, uint32_t bytes, uint32_t bar, uint64_t pol) {
    asm volatile("cp.async.bulk.shared::cluster.global.mbarrier::complete_tx::bytes.L2::cache_hint [%0], [%1], %2, [%3], %4;"
                 :: "r"(dst), "l"(src), "r"(bytes), "r"(bar), "l"(pol) : "memory");
}
__device__ __forceinline__ uint4 ldg_nc(const void* p) {
    uint4 v;
    asm volatile("ld.global.nc.L1::no_allocate.v4.u32 {%0,%1,%2,%3}, [%4];"
                 : "=r"(v.x), "=r"(v.y), "=r"(v.z), "=r"(v.w) : "l"(p));
    return v;
}
__device__ __forceinline__ void bulk_load_plain(uint32_t dst, const void* src, uint32_t bytes, uint32_t bar) {
    asm volatile("cp.async.bulk.shared::cluster.global.mbarrier::complete_tx::bytes [%0], [%1], %2, [%3];"
                 :: "r"(dst), "l"(src), "r"(bytes), "r"(bar) : "memory");
}
__device__ __forceinline__ uint32_t ldg_nc32(const void* p) {
    uint32_t v;
    asm volatile("ld.global.nc.L1::no_allocate.u32 %0, [%1];" : "=r"(v) : "l"(p));
    return v;
}
__device__ __forceinline__ uint32_t lds32(uint32_t addr) {
    uint32_t v;
    asm volatile("ld.volatile.shared.u32 %0, [%1];" : "=r"(v) : "r"(addr) : "memory");
    return v;
}
__device__ __forceinline__ uint32_t pin(uint32_t v) {
    uint32_t r;
    asm volatile("mov.b32 %0, %1;" : "=r"(r) : "r"(v));
    return r;
}
__device__ __forceinline__ uint32_t ld_relaxed32(const uint32_t* p) {
    uint32_t v;
    asm volatile("ld.relaxed.gpu.global.u32 %0, [%1];" : "=r"(v) : "l"(p) : "memory");
    return v;
}
__device__ __forceinline__ bool mbar_test(uint32_t bar, uint32_t parity) {
    uint32_t ok;
    asm volatile("{\n.reg .pred p;\nmbarrier.test_wait.parity.shared::cta.b64 p, [%1], %2;\nselp.u32 %0, 1, 0, p;\n}\n"
                 : "=r"(ok) : "r"(bar), "r"(parity) : "memory");
    return ok != 0;
}
__device__ __forceinline__ uint4 ld_relaxed(const uint4* p) {
    uint4 v;
    asm volatile("ld.relaxed.gpu.global.v4.u32 {%0,%1,%2,%3}, [%4];"
                 : "=r"(v.x), "=r"(v.y), "=r"(v.z), "=r"(v.w) : "l"(p) : "memory");
    return v;
}
__device__ __forceinline__ void st_relaxed(uint4* p, uint4 v) {
    asm volatile("st.relaxed.gpu.global.v4.u32 [%0], {%1,%2,%3,%4};"
                 :: "l"(p), "r"(v.x), "r"(v.y), "r"(v.z), "r"(v.w) : "memory");
}
__device__ __forceinline__ void ldsm_x4(uint32_t (&r)[4], uint32_t addr) {
    asm volatile("ldmatrix.sync.aligned.m8n8.x4.shared.b16 {%0,%1,%2,%3}, [%4];"
                 : "=r"(r[0]), "=r"(r[1]), "=r"(r[2]), "=r"(r[3]) : "r"(addr) : "memory");
}
__device__ __forceinline__ void ldsm_x4_t(uint32_t (&r)[4], uint32_t addr) {
    asm volatile("ldmatrix.sync.aligned.m8n8.x4.trans.shared.b16 {%0,%1,%2,%3}, [%4];"
                 : "=r"(r[0]), "=r"(r[1]), "=r"(r[2]), "=r"(r[3]) : "r"(addr) : "memory");
}
__device__ __forceinline__ void mma_bf16(float (&c)[4], const uint32_t (&a)[4], uint32_t b0, uint32_t b1) {
    asm volatile("mma.sync.aligned.m16n8k16.row.col.f32.bf16.bf16.f32 {%0,%1,%2,%3}, {%4,%5,%6,%7}, {%8,%9}, {%0,%1,%2,%3};"
                 : "+f"(c[0]), "+f"(c[1]), "+f"(c[2]), "+f"(c[3])
                 : "r"(a[0]), "r"(a[1]), "r"(a[2]), "r"(a[3]), "r"(b0), "r"(b1));
}
__device__ __forceinline__ float ex2(float x) {
    float r;
    asm("ex2.approx.ftz.f32 %0, %1;" : "=f"(r) : "f"(x));
    return r;
}
__device__ __forceinline__ uint32_t pack_bf16(float lo, float hi) {
    uint32_t r;
    asm("cvt.rn.bf16x2.f32 %0, %1, %2;" : "=r"(r) : "f"(hi), "f"(lo));
    return r;
}
__device__ __forceinline__ float bf_lo(uint32_t w) { return __uint_as_float(w << 16); }
__device__ __forceinline__ float bf_hi(uint32_t w) { return __uint_as_float(w & 0xffff0000u); }
__device__ __forceinline__ float bf16r(float x) { return __bfloat162float(__float2bfloat16_rn(x)); }
__device__ __forceinline__ float silu_f(float x) { return x / (1.0f + __expf(-x)); }

__device__ __forceinline__ void warp_layernorm(const uint4 a, const uint4 b, float (&xn)[16]) {
    float v[16];
    v[0] = bf_lo(a.x); v[1] = bf_hi(a.x); v[2] = bf_lo(a.y); v[3] = bf_hi(a.y);
    v[4] = bf_lo(a.z); v[5] = bf_hi(a.z); v[6] = bf_lo(a.w); v[7] = bf_hi(a.w);
    v[8] = bf_lo(b.x); v[9] = bf_hi(b.x); v[10] = bf_lo(b.y); v[11] = bf_hi(b.y);
    v[12] = bf_lo(b.z); v[13] = bf_hi(b.z); v[14] = bf_lo(b.w); v[15] = bf_hi(b.w);
    float s = 0.f;
#pragma unroll
    for (int i = 0; i < 16; i++) s += v[i];
#pragma unroll
    for (int o = 16; o; o >>= 1) s += __shfl_xor_sync(0xffffffffu, s, o);
    const float mean = s * (1.0f / DM);
    float ss = 0.f;
#pragma unroll
    for (int i = 0; i < 16; i++) { const float d = v[i] - mean; ss = fmaf(d, d, ss); }
#pragma unroll
    for (int o = 16; o; o >>= 1) ss += __shfl_xor_sync(0xffffffffu, ss, o);
    const float m_bf = bf16r(mean);
    const float den = bf16r(sqrtf(bf16r(bf16r(ss * (1.0f / DM)) + 1e-5f)));
#pragma unroll
    for (int i = 0; i < 16; i++) xn[i] = bf16r(__fdiv_rn(bf16r(v[i] - m_bf), den));
}

__device__ __forceinline__ bool ll_valid(const uint4& v, uint32_t tag) { return v.y == tag && v.w == tag; }

__device__ __forceinline__ void ffn_cta(uint8_t* smem, int f, uint32_t tag,
                                        const __nv_bfloat16* __restrict__ x,
                                        const __nv_bfloat16* __restrict__ w1,
                                        const __nv_bfloat16* __restrict__ w2) {
    const int tid = threadIdx.x, warp = tid >> 5, lane = tid & 31;
    const uint32_t sbase = smem_u32(smem), bar = sbase + FFN_BAR;
    float* xnT = reinterpret_cast<float*>(smem + FFN_XN);
    float* hT  = reinterpret_cast<float*>(smem + FFN_H);
    float* red = reinterpret_cast<float*>(smem + FFN_RED);
    if (tid == 0) {
#pragma unroll
        for (int s = 0; s < NBF; s++) mbar_init(bar + s * 8, 1);
    }
    __syncthreads();
    auto issue = [&](int c) {
        const int s = c % NBF;
        if (tid == 0) mbar_expect_tx(bar + s * 8, FFN_CHUNK);
        if (c < 8) {
            __syncthreads();
            if (tid < 64) bulk_load_plain(sbase + s * FFN_CHUNK + tid * (FS * 2), w1 + (size_t)(c * 64 + tid) * FF + f * FS, FS * 2, bar + s * 8);
        } else if (tid == 0) {
            bulk_load_plain(sbase + s * FFN_CHUNK, w2 + (size_t)(f * FS + (c - 8) * 43) * DM, FFN_CHUNK, bar + s * 8);
        }
    };
    for (int c = 0; c < NBF; c++) issue(c);
    if (warp < NB) {
        float xn[16];
        const uint4 xa = ldg_nc(x + warp * DM + lane * 16), xb = ldg_nc(x + warp * DM + lane * 16 + 8);
        warp_layernorm(xa, xb, xn);
#pragma unroll
        for (int i = 0; i < 16; i++) xnT[(lane * 16 + i) * 4 + warp] = xn[i];
    }
    __syncthreads();
    float acc[4][8];
#pragma unroll
    for (int b = 0; b < 4; b++)
#pragma unroll
        for (int c = 0; c < 8; c++) acc[b][c] = 0.f;
#pragma unroll 1
    for (int c = 0; c < 16; c++) {
        const int s = c % NBF;
        mbar_wait(bar + s * 8, (c / NBF) & 1);
        const bool st1 = c < 8;
        const int cg = st1 ? tid % 43 : (tid & 63), r0 = st1 ? tid / 43 : (tid >> 6);
        const int rstep = st1 ? 5 : 4, nrows = st1 ? 64 : 43, rbytes = st1 ? FS * 2 : DM * 2;
        const float* vec = st1 ? xnT + c * 64 * 4 : hT + (c - 8) * 43 * 4;
        const uint8_t* wb = smem + s * FFN_CHUNK + cg * 16;
        if (!st1 || tid < 43 * 5) {
#pragma unroll 2
            for (int k = r0; k < nrows; k += rstep) {
                const uint4 w = *reinterpret_cast<const uint4*>(wb + k * rbytes);
                const float4 xv = *reinterpret_cast<const float4*>(vec + k * 4);
                const float wf[8] = {bf_lo(w.x), bf_hi(w.x), bf_lo(w.y), bf_hi(w.y), bf_lo(w.z), bf_hi(w.z), bf_lo(w.w), bf_hi(w.w)};
#pragma unroll
                for (int j = 0; j < 8; j++) {
                    acc[0][j] = fmaf(xv.x, wf[j], acc[0][j]);
                    acc[1][j] = fmaf(xv.y, wf[j], acc[1][j]);
                    acc[2][j] = fmaf(xv.z, wf[j], acc[2][j]);
                    acc[3][j] = fmaf(xv.w, wf[j], acc[3][j]);
                }
            }
        }
        __syncthreads();
        if (c + NBF < 16) issue(c + NBF);
        if (c == 7) {
            if (tid < 43 * 5) {
#pragma unroll
                for (int b = 0; b < 4; b++)
#pragma unroll
                    for (int j = 0; j < 8; j++) red[(r0 * 4 + b) * FS + cg * 8 + j] = acc[b][j];
            }
#pragma unroll
            for (int b = 0; b < 4; b++)
#pragma unroll
                for (int j = 0; j < 8; j++) acc[b][j] = 0.f;
            __syncthreads();
            for (int i = tid; i < 4 * FS; i += NTHREADS) {
                const int b = i / FS, cc = i % FS;
                float sum = 0.f;
#pragma unroll
                for (int ks = 0; ks < 5; ks++) sum += red[(ks * 4 + b) * FS + cc];
                hT[cc * 4 + b] = bf16r(silu_f(bf16r(sum)));
            }
            __syncthreads();
        }
    }
    {
        const int cg = tid & 63, fs = tid >> 6;
#pragma unroll
        for (int b = 0; b < 4; b++)
#pragma unroll
            for (int j = 0; j < 8; j++) red[(fs * 4 + b) * DM + cg * 8 + j] = acc[b][j];
    }
    __syncthreads();
    for (int i = tid; i < NB * 256; i += NTHREADS) {
        const int b = i >> 8, j = (i >> 3) & 31, p = i & 7;
        float s0 = 0.f, s1 = 0.f;
#pragma unroll
        for (int fs = 0; fs < 4; fs++) { s0 += red[(fs * 4 + b) * DM + 16 * j + p]; s1 += red[(fs * 4 + b) * DM + 16 * j + 8 + p]; }
        st_relaxed(&g_ffn_part[((b * 32 + j) * N_FFN + f) * 8 + p],
                   make_uint4(__float_as_uint(s0), tag, __float_as_uint(s1), tag));
    }
}

__global__ void __launch_bounds__(NTHREADS, 1)
fused_decode_kernel(const __nv_bfloat16* __restrict__ x, const __nv_bfloat16* __restrict__ Kc,
                    const __nv_bfloat16* __restrict__ Vc, const __nv_bfloat16* __restrict__ wq,
                    const __nv_bfloat16* __restrict__ wo, const __nv_bfloat16* __restrict__ w1,
                    const __nv_bfloat16* __restrict__ w2, __nv_bfloat16* __restrict__ out) {
    extern __shared__ __align__(1024) uint8_t smem[];
    const int cta = blockIdx.x;
    const int tid = threadIdx.x, warp = tid >> 5, lane = tid & 31;
    if (cta >= N_ATT) {
        const uint32_t tag = ld_relaxed32(&g_epoch[cta]);
        ffn_cta(smem, cta - N_ATT, tag, x, w1, w2);
        if (tid == 0) { g_epoch[cta] = tag + 1; }
        return;
    }

    const int b = cta & 3, h = cta >> 2;
    const int bh = b * NH + h;
    const uint32_t sbase = pin(smem_u32(smem));
    const uint32_t bar_full = sbase + OFF_BAR;
    const uint32_t cnt_rel = bar_full + NST * 8;
    const char* kp = reinterpret_cast<const char*>(Kc) + (size_t)bh * SK * DH * 2;
    const char* vp = reinterpret_cast<const char*>(Vc) + (size_t)bh * SK * DH * 2;
    const char* wop = reinterpret_cast<const char*>(wo) + (size_t)h * DH * DM * 2;
    uint64_t pol;
    asm volatile("createpolicy.fractional.L2::evict_first.b64 %0, 1.0;" : "=l"(pol));
    auto issue_kv = [&](const char* src, int s) {
        const uint32_t bar = bar_full + s * 8;
        mbar_expect_tx(bar, STAGE_BYTES);
        bulk_load(sbase + s * STAGE_BYTES, src, STAGE_BYTES, bar, pol);
    };
    auto issue_first = [&](int n) { issue_kv(((n & 1) ? vp : kp) + (size_t)(n >> 1) * STAGE_BYTES, n); };
    const uint32_t bar_w = bar_full + 216, cnt_w = bar_full + 224;
    auto issue_w = [&](int q) {
        mbar_expect_tx(bar_w, STAGE_BYTES);
        bulk_load_plain(sbase + OFF_W, wop + (size_t)q * STAGE_BYTES, STAGE_BYTES, bar_w);
    };

    const int g = lane >> 2, t = lane & 3;
    float* xn_s  = reinterpret_cast<float*>(smem + OFF_XN);
    float* red_s = reinterpret_cast<float*>(smem + OFF_RED);
    __nv_bfloat16* q_s = reinterpret_cast<__nv_bfloat16*>(smem + OFF_Q);
    float* ml_s = reinterpret_cast<float*>(smem + OFF_ML);
    __nv_bfloat16* o_s = reinterpret_cast<__nv_bfloat16*>(smem + OFF_O);

    uint4* const q_out = &g_q_part[(h * NB + (lane >> 3)) * 32 + b * 8 + (lane & 7)];
    uint4* const a_out = &g_attn_part[((b * 32 + warp * 4 + t) * NH + h) * 8 + g];

    volatile uint32_t* q_flag = reinterpret_cast<volatile uint32_t*>(smem + OFF_BAR + 192);
    const uint32_t bar_x = bar_full + 200;
    if (tid == 0) {
        mbar_init(bar_full, 1);
        issue_first(0);
        mbar_init(bar_x, 1);
        mbar_expect_tx(bar_x, NB * DM * 2);
        bulk_load_plain(sbase + OFF_X, x, NB * DM * 2, bar_x);
#pragma unroll
        for (int s = 1; s < NST; s++) mbar_init(bar_full + s * 8, 1);
        mbar_init(bar_w, 1);
#pragma unroll
        for (int s = 0; s < NST; s++) *reinterpret_cast<volatile uint32_t*>(smem + OFF_BAR + NST * 8 + s * 4) = 0;
        *reinterpret_cast<volatile uint32_t*>(smem + OFF_BAR + 224) = 0;
        *q_flag = 0;
#pragma unroll 1
        for (int s = 1; s < FK_PRE; s++) issue_first(s);
    }
    uint32_t qf[8][2];
    uint32_t tag;
    {
        uint32_t w[32];
        const __nv_bfloat16* wp = wq + (size_t)(warp * 64 + (lane >> 4) * 32) * (NH * DH) + h * DH + b * 32 + (lane & 15) * 2;
#pragma unroll
        for (int i = 0; i < 32; i++) w[i] = ldg_nc32(wp + (size_t)i * (NH * DH));
        tag = ld_relaxed32(&g_epoch[cta]);
        if (tid == 0) {
#pragma unroll 1
            for (int s = FK_PRE; s < FK_FIRST; s++) issue_first(s);
            asm volatile("prefetch.global.L2 [%0];" :: "l"(wop));
        }
        if (warp == 0) st_relaxed(q_out, make_uint4(0, 0, 0, 0));
        if (FK_INIT_AT < 0) st_relaxed(a_out, make_uint4(0, 0, 0, 0));
        __syncthreads();
        if (warp < 4) {
            float xn[16];
            mbar_wait(bar_x, 0);
            const uint4 xa = *reinterpret_cast<const uint4*>(smem + OFF_X + warp * DM * 2 + lane * 32);
            const uint4 xb = *reinterpret_cast<const uint4*>(smem + OFF_X + warp * DM * 2 + lane * 32 + 16);
            warp_layernorm(xa, xb, xn);
#pragma unroll
            for (int i = 0; i < 16; i += 4)
                *reinterpret_cast<float4*>(xn_s + warp * DM + lane * 16 + i) = make_float4(xn[i], xn[i + 1], xn[i + 2], xn[i + 3]);
        }
        __syncthreads();
        float acc[4][2];
#pragma unroll
        for (int bb = 0; bb < 4; bb++) acc[bb][0] = acc[bb][1] = 0.f;
        const float* xp = xn_s + warp * 64 + (lane >> 4) * 32;
#pragma unroll
        for (int i4 = 0; i4 < 8; i4++) {
#pragma unroll
            for (int bb = 0; bb < 4; bb++) {
                const float4 xv = *reinterpret_cast<const float4*>(xp + bb * DM + i4 * 4);
                const float xs[4] = {xv.x, xv.y, xv.z, xv.w};
#pragma unroll
                for (int u = 0; u < 4; u++) {
                    acc[bb][0] = fmaf(xs[u], bf_lo(w[i4 * 4 + u]), acc[bb][0]);
                    acc[bb][1] = fmaf(xs[u], bf_hi(w[i4 * 4 + u]), acc[bb][1]);
                }
            }
        }
        const bool up = lane >= 16;
        float k0 = up ? acc[2][0] : acc[0][0], k1 = up ? acc[2][1] : acc[0][1];
        float k2 = up ? acc[3][0] : acc[1][0], k3 = up ? acc[3][1] : acc[1][1];
        k0 += __shfl_xor_sync(0xffffffffu, up ? acc[0][0] : acc[2][0], 16);
        k1 += __shfl_xor_sync(0xffffffffu, up ? acc[0][1] : acc[2][1], 16);
        k2 += __shfl_xor_sync(0xffffffffu, up ? acc[1][0] : acc[3][0], 16);
        k3 += __shfl_xor_sync(0xffffffffu, up ? acc[1][1] : acc[3][1], 16);
        float* rp = red_s + warp * 128 + (up ? 64 : 0) + (lane & 15) * 2;
        *reinterpret_cast<float2*>(rp)      = make_float2(k0, k1);
        *reinterpret_cast<float2*>(rp + 32) = make_float2(k2, k3);
        __syncthreads();
        if (warp == 0) {
            float4 s = make_float4(0.f, 0.f, 0.f, 0.f);
#pragma unroll
            for (int w8 = 0; w8 < NCW; w8++) {
                const float4 v = *reinterpret_cast<const float4*>(red_s + w8 * 128 + lane * 4);
                s.x += v.x; s.y += v.y; s.z += v.z; s.w += v.w;
            }
            st_relaxed(q_out, make_uint4(pack_bf16(s.x, s.y), tag, pack_bf16(s.z, s.w), tag));
            const uint4* p = &g_q_part[(h * NB + b) * 32 + lane];
            uint4 v = ld_relaxed(p);
            for (int spin = 0; !ll_valid(v, tag) && spin < (1 << 20); spin++) v = ld_relaxed(p);
            *reinterpret_cast<uint2*>(q_s + lane * 4) = make_uint2(v.x, v.z);
            if (lane == 0) *q_flag = 1;
        }
        if (tid == NTHREADS - 32) {
            int next = FK_FIRST, watch = 0;
            while (next < NST) {
                if (mbar_test(bar_full + watch * 8, 0)) { issue_first(next); next++; watch++; }
                else if (*q_flag) break;
            }
#pragma unroll 1
            for (; next < NST; next++) issue_first(next);
        }
        __syncthreads();
#pragma unroll
        for (int j = 0; j < 8; j++) {
            const int c = (j ^ g) & 7;
            qf[j][0] = *reinterpret_cast<const uint32_t*>(q_s + c * 8 + 2 * t);
            qf[j][1] = *reinterpret_cast<const uint32_t*>(q_s + 64 + c * 8 + 2 * t);
        }
    }

    constexpr float RSQRT_DH = 0.08838834764831845f, LOG2E = 1.4426950408889634f;
    const int li = lane & 7, lm = lane >> 3;
    const uint32_t k_base = pin(sbase + (uint32_t)((warp * 16 + li + 8 * (lm & 1)) * 256 + (lm >> 1) * 128 + li * 16));
    const uint32_t v_base = pin(sbase + (uint32_t)((warp * 16 + li + 8 * (lm >> 1)) * 256 + (lm & 1) * 128 + li * 16));
    const bool diag = (t == (g >> 1));
    uint32_t msk[8];
#pragma unroll
    for (int j = 0; j < 8; j++) msk[j] = pin((j == (g ^ (2 * t)) ? 0x0000ffffu : 0u) | (j == (g ^ (2 * t) ^ 1) ? 0xffff0000u : 0u));
    const uint32_t ones[4] = {0x3f803f80u, 0x3f803f80u, 0x3f803f80u, 0x3f803f80u};

    float acc0[4] = {0.f, 0.f, 0.f, 0.f}, acc1[4] = {0.f, 0.f, 0.f, 0.f}, lacc[4] = {0.f, 0.f, 0.f, 0.f};
    float m_raw = -INFINITY;
    float m_run = -INFINITY, mc = 0.f;
    float fin_scale = 0.f;
    int st = 0; uint32_t ph = 0;
    int seq = NST;
    uint32_t wa[8][4][4];
    float g0 = 0.f, g1 = 0.f;
    uint4 gv = make_uint4(0, 0, 0, 0);
    const int cp = lane & 7, q4 = lane >> 3;
    const float x0 = __bfloat162float(reinterpret_cast<const __nv_bfloat16*>(smem + OFF_X)[b * DM + h * 16 + cp]);
    const float x1 = __bfloat162float(reinterpret_cast<const __nv_bfloat16*>(smem + OFF_X)[b * DM + h * 16 + 8 + cp]);
    const uint32_t prog_base = (tag - 1) * (uint32_t)(N_ATT * NT);
    const uint32_t prog_s = bar_full + 208;
    uint32_t prog_v = prog_base;
    if (tid == 0) *reinterpret_cast<volatile uint32_t*>(smem + OFF_BAR + 208) = prog_base;
    __syncthreads();
    auto pace = [&](uint32_t pv, uint32_t lim) {
        for (int spin = 0; (int)(pv - lim) < 0 && spin < 4096; spin++) pv = ld_relaxed32(&g_progress[0]);
    };

#pragma unroll 1
    for (int it = 0; it < NT; it++) {
#pragma unroll
        for (int q = 0; q <= 4; q++) {
            if (it == FK_WTILE + q * FK_WSTEP) {
                if (q == 0) {
                    if (tid == 0) {
                        asm volatile("fence.proxy.async.shared::cta;" ::: "memory");
                        issue_w(0);
                    }
                } else {
                    mbar_wait(bar_w, (q - 1) & 1);
                    const uint32_t wb = sbase + OFF_W + (li + 8 * (lane >> 4)) * 1024 + warp * 128 + (lm & 1) * 16;
#pragma unroll
                    for (int j = 0; j < 4; j++) {
                        ldsm_x4_t(wa[2 * q - 2][j], wb + j * 32);
                        ldsm_x4_t(wa[2 * q - 1][j], wb + 16384 + j * 32);
                    }
                    if (q < 4 && lane == 0) {
                        const uint32_t rel = atom_inc_shared(cnt_w);
                        if ((rel & (NCW - 1)) == NCW - 1) issue_w(q);
                    }
                }
                __syncwarp();
            }
        }
        if (it == FK_INIT_AT) st_relaxed(a_out, make_uint4(0, 0, 0, 0));
        if (it == NT - 12 && warp == 0) {
            gv = ld_relaxed(&g_ffn_part[((b * 32 + h) * N_FFN + q4) * 8 + cp]);
        }
        if (it == NT - 2 && warp == 0) {
            const uint4* p = &g_ffn_part[((b * 32 + h) * N_FFN + q4) * 8 + cp];
            uint4 v = gv;
            for (int spin = 0; !ll_valid(v, tag) && spin < (1 << 20); spin++) { __nanosleep(64); v = ld_relaxed(p); }
            __syncwarp();
            g0 = __uint_as_float(v.x); g1 = __uint_as_float(v.z);
            g0 += __shfl_xor_sync(0xffffffffu, g0, 8);  g1 += __shfl_xor_sync(0xffffffffu, g1, 8);
            g0 += __shfl_xor_sync(0xffffffffu, g0, 16); g1 += __shfl_xor_sync(0xffffffffu, g1, 16);
            g0 = bf16r(silu_f(bf16r(g0))); g1 = bf16r(silu_f(bf16r(g1)));
        }
        if (tid == 0) {
            *reinterpret_cast<volatile uint32_t*>(smem + OFF_BAR + 208) = prog_v;
            prog_v = ld_relaxed32(&g_progress[0]);
        }
        const bool endgame = it >= NT - FK_ENDT;
        const char* k_next = kp + (size_t)(it + NST / 2) * STAGE_BYTES;
        const char* v_next = vp + (size_t)(it + NST / 2) * STAGE_BYTES;
        mbar_wait(bar_full + st * 8, ph);
        float c0[4] = {0.f, 0.f, 0.f, 0.f}, c1[4] = {0.f, 0.f, 0.f, 0.f};
        uint32_t relK = 0, pvK = 0;
        const uint32_t kb = k_base + st * STAGE_BYTES;
        {
#pragma unroll
            for (int j = 0; j < 8; j++) {
                uint32_t a[4];
                ldsm_x4(a, kb ^ (j << 4));
                mma_bf16((j & 1) ? c1 : c0, a, qf[j][0], qf[j][1]);
            }
            if (!endgame && seq < NSEQ && lane == 0) {
                relK = atom_inc_shared(cnt_rel + st * 4);
                pvK = lds32(prog_s);
            }
        }
        const float u0 = (g & 1) ? (c0[1] + c1[1]) : (c0[0] + c1[0]);
        const float u1 = (g & 1) ? (c0[3] + c1[3]) : (c0[2] + c1[2]);
        int key = __float_as_int(diag ? fmaxf(u0, u1) : -INFINITY);
        key ^= (key >> 31) & 0x7fffffff;
        key = __reduce_max_sync(0xffffffffu, key);
        const uint32_t r1 = pack_bf16(u0, u1);
        const uint32_t r2 = pack_bf16(bf_lo(r1) * RSQRT_DH, bf_hi(r1) * RSQRT_DH);
        const float s0 = diag ? bf_lo(r2) : -INFINITY, s1 = diag ? bf_hi(r2) : -INFINITY;
        key ^= (key >> 31) & 0x7fffffff;
        const float tmax = __int_as_float(key);
        if (tmax > m_raw) {
            m_raw = tmax;
            const float m_new = bf16r(bf16r(tmax) * RSQRT_DH);
            const float sc = ex2((m_run - m_new) * LOG2E);
#pragma unroll
            for (int i = 0; i < 4; i++) { acc0[i] *= sc; acc1[i] *= sc; }
            lacc[0] *= sc;
            m_run = m_new;
            mc = -m_new * LOG2E;
        }
        const uint32_t pk = pack_bf16(ex2(fmaf(s0, LOG2E, mc)), ex2(fmaf(s1, LOG2E, mc)));
        const uint32_t xx = __shfl_sync(0xffffffffu, pk, 9 * t), yy = __shfl_sync(0xffffffffu, pk, 9 * t + 4);
        const uint32_t pp0 = __byte_perm(xx, yy, 0x5410), pp1 = __byte_perm(xx, yy, 0x7632);
        if ((relK & (NCW - 1)) == NCW - 1) {
            pace(pvK, prog_base + (uint32_t)(it * N_ATT - (FK_LEAD)));
            issue_kv(k_next, st);
        }
        __syncwarp();
        const int stK = st;
        seq++;
        if (++st == NST) { st = 0; ph ^= 1; }
        mma_bf16(lacc, ones, pp0, pp1);
        if (it == NT - 1) {
            if (lane == 0) { ml_s[warp] = m_run; ml_s[8 + warp] = lacc[0]; }
            __syncthreads();
            const float4 ma = *reinterpret_cast<const float4*>(ml_s), mb = *reinterpret_cast<const float4*>(ml_s + 4);
            const float4 la = *reinterpret_cast<const float4*>(ml_s + 8), lb = *reinterpret_cast<const float4*>(ml_s + 12);
            const float M = fmaxf(fmaxf(fmaxf(ma.x, ma.y), fmaxf(ma.z, ma.w)), fmaxf(fmaxf(mb.x, mb.y), fmaxf(mb.z, mb.w)));
            const float L = (ex2((ma.x - M) * LOG2E) * la.x + ex2((ma.y - M) * LOG2E) * la.y) + (ex2((ma.z - M) * LOG2E) * la.z + ex2((ma.w - M) * LOG2E) * la.w)
                          + (ex2((mb.x - M) * LOG2E) * lb.x + ex2((mb.y - M) * LOG2E) * lb.y) + (ex2((mb.z - M) * LOG2E) * lb.z + ex2((mb.w - M) * LOG2E) * lb.w);
            fin_scale = __fdividef(ex2((m_run - M) * LOG2E), L);
        }
        mbar_wait(bar_full + st * 8, ph);
        const uint32_t vb = v_base + st * STAGE_BYTES;
        {
            uint32_t relV = 0, pvV = 0;
#pragma unroll
            for (int j = 0; j < 8; j++) {
                uint32_t a[4];
                ldsm_x4_t(a, vb ^ (j << 4));
                mma_bf16((j & 1) ? acc1 : acc0, a, pp0 & msk[j], pp1 & msk[j]);
            }
            if (seq - (endgame ? 1 : 0) < NSEQ && lane == 0) {
                relV = atom_inc_shared(cnt_rel + st * 4);
                pvV = lds32(prog_s);
            }
            if (tid == NTHREADS - 32) asm volatile("red.relaxed.gpu.global.add.u32 [%0], 1;" :: "l"(&g_progress[0]) : "memory");
            if ((relV & (NCW - 1)) == NCW - 1) {
                if (endgame) {
                    pace(pvV, prog_base + (uint32_t)((it + 1) * N_ATT - (FK_LEAD_END)));
                    issue_kv(k_next, stK);
                }
                if (seq < NSEQ) issue_kv(v_next, st);
            }
        }
        __syncwarp();
        seq++;
        if (++st == NST) { st = 0; ph ^= 1; }
    }

    if ((prog_v ^ gv.x ^ gv.y ^ gv.z ^ gv.w) == 0x9e3779b9u) *reinterpret_cast<volatile uint32_t*>(smem + OFF_BAR + 240) = 0;
    const uint4* inbox = &g_attn_part[((b * 32 + h) * NH + q4 * 8) * 8 + cp];
    asm volatile("" : "+l"(inbox));
    {
        float* o = red_s + warp * 128;
        o[16 * t + g]          = (acc0[0] + acc1[0]) * fin_scale;
        o[16 * t + 8 + g]      = (acc0[1] + acc1[1]) * fin_scale;
        o[64 + 16 * t + g]     = (acc0[2] + acc1[2]) * fin_scale;
        o[64 + 16 * t + 8 + g] = (acc0[3] + acc1[3]) * fin_scale;
    }
    __syncthreads();
    if (tid < DH) {
        float v[8];
#pragma unroll
        for (int w = 0; w < 8; w++) v[w] = red_s[w * 128 + tid];
        const float o = ((v[0] + v[1]) + (v[2] + v[3])) + ((v[4] + v[5]) + (v[6] + v[7]));
        o_s[((tid >> 1) & 3) * 32 + (tid >> 4) * 4 + ((tid >> 3) & 1) * 2 + (tid & 1)] = __float2bfloat16_rn(o);
    }
    __syncthreads();
    {
        float d[4][4];
#pragma unroll
        for (int j = 0; j < 4; j++) { d[j][0] = d[j][1] = d[j][2] = d[j][3] = 0.f; }
        uint4 ov[4];
#pragma unroll
        for (int i = 0; i < 4; i++) ov[i] = *reinterpret_cast<const uint4*>(o_s + t * 32 + i * 8);
#pragma unroll
        for (int i = 0; i < 4; i++) {
#pragma unroll
            for (int j = 0; j < 4; j++) mma_bf16(d[j], wa[2 * i][j], ov[i].x, ov[i].y);
#pragma unroll
            for (int j = 0; j < 4; j++) mma_bf16(d[j], wa[2 * i + 1][j], ov[i].z, ov[i].w);
        }
        float r0 = d[0][0], r1 = d[0][2];
        if (t == 1) { r0 = d[1][0]; r1 = d[1][2]; }
        if (t == 2) { r0 = d[2][0]; r1 = d[2][2]; }
        if (t == 3) { r0 = d[3][0]; r1 = d[3][2]; }
        st_relaxed(a_out, make_uint4(__float_as_uint(r0), tag, __float_as_uint(r1), tag));
    }
    if (warp == 0) {
        const uint4* p = inbox;
        uint4 v[8];
#pragma unroll
        for (int i = 0; i < 8; i++) v[i] = ld_relaxed(p + i * 8);
#pragma unroll 1
        for (int spin = 0; spin < (1 << 20); spin++) {
            uint32_t bad[8];
#pragma unroll
            for (int i = 0; i < 8; i++) bad[i] = (v[i].y ^ tag) | (v[i].w ^ tag);
            if ((((bad[0] | bad[1]) | (bad[2] | bad[3])) | ((bad[4] | bad[5]) | (bad[6] | bad[7]))) == 0) break;
#pragma unroll
            for (int i = 0; i < 8; i++) {
                if (bad[i] != 0) v[i] = ld_relaxed(p + i * 8);
            }
        }
        __syncwarp();
        float s0 = ((__uint_as_float(v[0].x) + __uint_as_float(v[1].x)) + (__uint_as_float(v[2].x) + __uint_as_float(v[3].x)))
                 + ((__uint_as_float(v[4].x) + __uint_as_float(v[5].x)) + (__uint_as_float(v[6].x) + __uint_as_float(v[7].x)));
        float s1 = ((__uint_as_float(v[0].z) + __uint_as_float(v[1].z)) + (__uint_as_float(v[2].z) + __uint_as_float(v[3].z)))
                 + ((__uint_as_float(v[4].z) + __uint_as_float(v[5].z)) + (__uint_as_float(v[6].z) + __uint_as_float(v[7].z)));
        s0 += __shfl_xor_sync(0xffffffffu, s0, 8);  s1 += __shfl_xor_sync(0xffffffffu, s1, 8);
        s0 += __shfl_xor_sync(0xffffffffu, s0, 16); s1 += __shfl_xor_sync(0xffffffffu, s1, 16);
        const uint32_t sb = pack_bf16(s0, s1);
        const uint32_t sg = pack_bf16(bf_lo(sb) * g0, bf_hi(sb) * g1);
        const uint32_t ob = pack_bf16(x0 + bf_lo(sg), x1 + bf_hi(sg));
        const int src = (2 * lane) & 7;
        const uint32_t e0 = __shfl_sync(0xffffffffu, ob, src), e1 = __shfl_sync(0xffffffffu, ob, src + 1);
        if (lane < 8)
            *reinterpret_cast<uint32_t*>(out + b * DM + h * 16 + 2 * lane) = __byte_perm(e0, e1, lane < 4 ? 0x5410 : 0x7632);
        if (lane == 0) { g_epoch[cta] = tag + 1; }
    }
}

}

extern "C" void kernel_launch(void* const* d_in, const int* in_sizes, int n_in, void* d_out, int out_size) {
    (void)in_sizes; (void)n_in; (void)out_size;
    const __nv_bfloat16* x  = (const __nv_bfloat16*)d_in[0];
    const __nv_bfloat16* Kc = (const __nv_bfloat16*)d_in[1];
    const __nv_bfloat16* Vc = (const __nv_bfloat16*)d_in[2];
    const __nv_bfloat16* wq = (const __nv_bfloat16*)d_in[3];
    const __nv_bfloat16* wo = (const __nv_bfloat16*)d_in[4];
    const __nv_bfloat16* w1 = (const __nv_bfloat16*)d_in[6];
    const __nv_bfloat16* w2 = (const __nv_bfloat16*)d_in[7];

    static bool attr_set = false;
    if (!attr_set) {
        cudaFuncSetAttribute(fk::fused_decode_kernel, cudaFuncAttributeMaxDynamicSharedMemorySize, fk::SMEM_BYTES);
        attr_set = true;
    }
    fk::fused_decode_kernel<<<fk::N_CTA, fk::NTHREADS, fk::SMEM_BYTES>>>(x, Kc, Vc, wq, wo, w1, w2, (__nv_bfloat16*)d_out);
}
```

```cpp
#include <cuda_runtime.h>
#include <cuda_bf16.h>
#include <stdint.h>

namespace fk {

#define FK_NST 4
#define FK_FIRST 2
#define FK_PRE 1
#define FK_INIT_AT 56
#define FK_WTILE 4
#define FK_WSTEP 10
#define FK_LEAD 0
#define FK_ENDT 16
#define FK_LEAD_END 48

constexpr int NB = 4, NH = 32, SK = 8192, DH = 128, DM = 512, FF = 1376;
constexpr int TK = 128;
constexpr int NT = SK / TK;
constexpr int STAGE_BYTES = TK * DH * 2;
constexpr int NST = FK_NST;
constexpr int NCW = 8;
constexpr int NTHREADS = NCW * 32;
constexpr int N_ATT = NB * NH;
constexpr int N_FFN = 4;
constexpr int FS = FF / N_FFN;
constexpr int N_CTA = N_ATT + N_FFN;
constexpr int NSEQ = 2 * NT;
static_assert(NST % 2 == 0, "K tiles live in the even stages, V tiles in the odd ones");

constexpr int OFF_W   = NST * STAGE_BYTES;
constexpr int OFF_XN  = OFF_W;
constexpr int OFF_X   = OFF_W + 8192;
constexpr int OFF_RED = OFF_W + 12288;
constexpr int OFF_BAR = OFF_W + STAGE_BYTES;
constexpr int OFF_Q   = OFF_BAR + 256;
constexpr int OFF_ML  = OFF_Q + 256;
constexpr int OFF_O   = OFF_ML + 64;
constexpr int SMEM_ATT = OFF_O + 256;
constexpr int FFN_CHUNK = 64 * FS * 2;
constexpr int NBF = (NST >= 6) ? 4 : 2;
constexpr int FFN_XN = NBF * FFN_CHUNK, FFN_H = FFN_XN + 8192, FFN_RED = FFN_H + 5504, FFN_BAR = FFN_RED + 32768;
constexpr int SMEM_FFN = FFN_BAR + 64;
static_assert(FFN_CHUNK == 43 * DM * 2, "chunk geometry");
constexpr int SMEM_BYTES = SMEM_ATT > SMEM_FFN ? SMEM_ATT : SMEM_FFN;

__device__ __align__(256) uint4 g_q_part[NH * NB * 32];
__device__ __align__(256) uint4 g_attn_part[NB * 32 * NH * 8];
__device__ __align__(256) uint4 g_ffn_part[NB * 32 * N_FFN * 8];
__device__ __align__(256) uint32_t g_progress[64];
#define FK_ONE4 1u, 1u, 1u, 1u
#define FK_ONE16 FK_ONE4, FK_ONE4, FK_ONE4, FK_ONE4
#define FK_ONE64 FK_ONE16, FK_ONE16, FK_ONE16, FK_ONE16
#define FK_ONE256 FK_ONE64, FK_ONE64, FK_ONE64, FK_ONE64
#define FK_ONE1024 FK_ONE256, FK_ONE256, FK_ONE256, FK_ONE256
__device__ __align__(256) uint32_t g_epoch[N_CTA * 32] = {FK_ONE1024, FK_ONE1024, FK_ONE1024, FK_ONE1024, FK_ONE64, FK_ONE64};

__device__ __forceinline__ uint32_t smem_u32(const void* p) { return (uint32_t)__cvta_generic_to_shared(p); }

__device__ __forceinline__ void mbar_init(uint32_t bar, uint32_t cnt) {
    asm volatile("mbarrier.init.shared::cta.b64 [%0], %1;" :: "r"(bar), "r"(cnt) : "memory");
}
__device__ __forceinline__ void mbar_expect_tx(uint32_t bar, uint32_t bytes) {
    asm volatile("mbarrier.arrive.expect_tx.shared::cta.b64 _, [%0], %1;" :: "r"(bar), "r"(bytes) : "memory");
}
__device__ __forceinline__ uint32_t atom_inc_shared(uint32_t addr) {
    uint32_t old;
    asm volatile("atom.relaxed.cta.shared::cta.add.u32 %0, [%1], 1;" : "=r"(old) : "r"(addr) : "memory");
    return old;
}
__device__ __forceinline__ void mbar_wait(uint32_t bar, uint32_t parity) {
    asm volatile(
        "{\n"
        ".reg .pred p;\n"
        "FK_WAIT:\n"
        "mbarrier.try_wait.parity.shared::cta.b64 p, [%0], %1;\n"
        "@p bra FK_DONE;\n"
        "bra FK_WAIT;\n"
        "FK_DONE:\n"
        "}\n" :: "r"(bar), "r"(parity) : "memory");
}
__device__ __forceinline__ void bulk_load(uint32_t dst, const void* src, uint32_t bytes, uint32_t bar, uint64_t pol) {
    asm volatile("cp.async.bulk.shared::cluster.global.mbarrier::complete_tx::bytes.L2::cache_hint [%0], [%1], %2, [%3], %4;"
                 :: "r"(dst), "l"(src), "r"(bytes), "r"(bar), "l"(pol) : "memory");
}
__device__ __forceinline__ uint4 ldg_nc(const void* p) {
    uint4 v;
    asm volatile("ld.global.nc.L1::no_allocate.v4.u32 {%0,%1,%2,%3}, [%4];"
                 : "=r"(v.x), "=r"(v.y), "=r"(v.z), "=r"(v.w) : "l"(p));
    return v;
}
__device__ __forceinline__ void bulk_load_plain(uint32_t dst, const void* src, uint32_t bytes, uint32_t bar) {
    asm volatile("cp.async.bulk.shared::cluster.global.mbarrier::complete_tx::bytes [%0], [%1], %2, [%3];"
                 :: "r"(dst), "l"(src), "r"(bytes), "r"(bar) : "memory");
}
__device__ __forceinline__ uint32_t ldg_nc32(const void* p) {
    uint32_t v;
    asm volatile("ld.global.nc.L1::no_allocate.u32 %0, [%1];" : "=r"(v) : "l"(p));
    return v;
}
__device__ __forceinline__ uint32_t lds32(uint32_t addr) {
    uint32_t v;
    asm volatile("ld.volatile.shared.u32 %0, [%1];" : "=r"(v) : "r"(addr) : "memory");
    return v;
}
__device__ __forceinline__ uint32_t pin(uint32_t v) {
    uint32_t r;
    asm volatile("mov.b32 %0, %1;" : "=r"(r) : "r"(v));
    return r;
}
__device__ __forceinline__ uint32_t ld_relaxed32(const uint32_t* p) {
    uint32_t v;
    asm volatile("ld.relaxed.gpu.global.u32 %0, [%1];" : "=r"(v) : "l"(p) : "memory");
    return v;
}
__device__ __forceinline__ bool mbar_test(uint32_t bar, uint32_t parity) {
    uint32_t ok;
    asm volatile("{\n.reg .pred p;\nmbarrier.test_wait.parity.shared::cta.b64 p, [%1], %2;\nselp.u32 %0, 1, 0, p;\n}\n"
                 : "=r"(ok) : "r"(bar), "r"(parity) : "memory");
    return ok != 0;
}
__device__ __forceinline__ uint4 ld_relaxed(const uint4* p) {
    uint4 v;
    asm volatile("ld.relaxed.gpu.global.v4.u32 {%0,%1,%2,%3}, [%4];"
                 : "=r"(v.x), "=r"(v.y), "=r"(v.z), "=r"(v.w) : "l"(p) : "memory");
    return v;
}
__device__ __forceinline__ void st_relaxed(uint4* p, uint4 v) {
    asm volatile("st.relaxed.gpu.global.v4.u32 [%0], {%1,%2,%3,%4};"
                 :: "l"(p), "r"(v.x), "r"(v.y), "r"(v.z), "r"(v.w) : "memory");
}
__device__ __forceinline__ void ldsm_x4(uint32_t (&r)[4], uint32_t addr) {
    asm volatile("ldmatrix.sync.aligned.m8n8.x4.shared.b16 {%0,%1,%2,%3}, [%4];"
                 : "=r"(r[0]), "=r"(r[1]), "=r"(r[2]), "=r"(r[3]) : "r"(addr) : "memory");
}
__device__ __forceinline__ void ldsm_x4_t(uint32_t (&r)[4], uint32_t addr) {
    asm volatile("ldmatrix.sync.aligned.m8n8.x4.trans.shared.b16 {%0,%1,%2,%3}, [%4];"
                 : "=r"(r[0]), "=r"(r[1]), "=r"(r[2]), "=r"(r[3]) : "r"(addr) : "memory");
}
__device__ __forceinline__ void mma_bf16(float (&c)[4], const uint32_t (&a)[4], uint32_t b0, uint32_t b1) {
    asm volatile("mma.sync.aligned.m16n8k16.row.col.f32.bf16.bf16.f32 {%0,%1,%2,%3}, {%4,%5,%6,%7}, {%8,%9}, {%0,%1,%2,%3};"
                 : "+f"(c[0]), "+f"(c[1]), "+f"(c[2]), "+f"(c[3])
                 : "r"(a[0]), "r"(a[1]), "r"(a[2]), "r"(a[3]), "r"(b0), "r"(b1));
}
__device__ __forceinline__ float ex2(float x) {
    float r;
    asm("ex2.approx.ftz.f32 %0, %1;" : "=f"(r) : "f"(x));
    return r;
}
__device__ __forceinline__ uint32_t pack_bf16(float lo, float hi) {
    uint32_t r;
    asm("cvt.rn.bf16x2.f32 %0, %1, %2;" : "=r"(r) : "f"(hi), "f"(lo));
    return r;
}
__device__ __forceinline__ float bf_lo(uint32_t w) { return __uint_as_float(w << 16); }
__device__ __forceinline__ float bf_hi(uint32_t w) { return __uint_as_float(w & 0xffff0000u); }
__device__ __forceinline__ float bf16r(float x) { return __bfloat162float(__float2bfloat16_rn(x)); }
__device__ __forceinline__ float silu_f(float x) { return x / (1.0f + __expf(-x)); }

__device__ __forceinline__ void warp_layernorm(const uint4 a, const uint4 b, float (&xn)[16]) {
    float v[16];
    v[0] = bf_lo(a.x); v[1] = bf_hi(a.x); v[2] = bf_lo(a.y); v[3] = bf_hi(a.y);
    v[4] = bf_lo(a.z); v[5] = bf_hi(a.z); v[6] = bf_lo(a.w); v[7] = bf_hi(a.w);
    v[8] = bf_lo(b.x); v[9] = bf_hi(b.x); v[10] = bf_lo(b.y); v[11] = bf_hi(b.y);
    v[12] = bf_lo(b.z); v[13] = bf_hi(b.z); v[14] = bf_lo(b.w); v[15] = bf_hi(b.w);
    float s = 0.f;
#pragma unroll
    for (int i = 0; i < 16; i++) s += v[i];
#pragma unroll
    for (int o = 16; o; o >>= 1) s += __shfl_xor_sync(0xffffffffu, s, o);
    const float mean = s * (1.0f / DM);
    float ss = 0.f;
#pragma unroll
    for (int i = 0; i < 16; i++) { const float d = v[i] - mean; ss = fmaf(d, d, ss); }
#pragma unroll
    for (int o = 16; o; o >>= 1) ss += __shfl_xor_sync(0xffffffffu, ss, o);
    const float m_bf = bf16r(mean);
    const float den = bf16r(sqrtf(bf16r(bf16r(ss * (1.0f / DM)) + 1e-5f)));
#pragma unroll
    for (int i = 0; i < 16; i++) xn[i] = bf16r(__fdiv_rn(bf16r(v[i] - m_bf), den));
}

__device__ __forceinline__ bool ll_valid(const uint4& v, uint32_t tag) { return v.y == tag && v.w == tag; }

__device__ __forceinline__ void ffn_cta(uint8_t* smem, int f, uint32_t tag,
                                        const __nv_bfloat16* __restrict__ x,
                                        const __nv_bfloat16* __restrict__ w1,
                                        const __nv_bfloat16* __restrict__ w2) {
    const int tid = threadIdx.x, warp = tid >> 5, lane = tid & 31;
    const uint32_t sbase = smem_u32(smem), bar = sbase + FFN_BAR;
    float* xnT = reinterpret_cast<float*>(smem + FFN_XN);
    float* hT  = reinterpret_cast<float*>(smem + FFN_H);
    float* red = reinterpret_cast<float*>(smem + FFN_RED);
    if (tid == 0) {
#pragma unroll
        for (int s = 0; s < NBF; s++) mbar_init(bar + s * 8, 1);
    }
    __syncthreads();
    auto issue = [&](int c) {
        const int s = c % NBF;
        if (tid == 0) mbar_expect_tx(bar + s * 8, FFN_CHUNK);
        if (c < 8) {
            __syncthreads();
            if (tid < 64) bulk_load_plain(sbase + s * FFN_CHUNK + tid * (FS * 2), w1 + (size_t)(c * 64 + tid) * FF + f * FS, FS * 2, bar + s * 8);
        } else if (tid == 0) {
            bulk_load_plain(sbase + s * FFN_CHUNK, w2 + (size_t)(f * FS + (c - 8) * 43) * DM, FFN_CHUNK, bar + s * 8);
        }
    };
    for (int c = 0; c < NBF; c++) issue(c);
    if (warp < NB) {
        float xn[16];
        const uint4 xa = ldg_nc(x + warp * DM + lane * 16), xb = ldg_nc(x + warp * DM + lane * 16 + 8);
        warp_layernorm(xa, xb, xn);
#pragma unroll
        for (int i = 0; i < 16; i++) xnT[(lane * 16 + i) * 4 + warp] = xn[i];
    }
    __syncthreads();
    float acc[4][8];
#pragma unroll
    for (int b = 0; b < 4; b++)
#pragma unroll
        for (int c = 0; c < 8; c++) acc[b][c] = 0.f;
#pragma unroll 1
    for (int c = 0; c < 16; c++) {
        const int s = c % NBF;
        mbar_wait(bar + s * 8, (c / NBF) & 1);
        const bool st1 = c < 8;
        const int cg = st1 ? tid % 43 : (tid & 63), r0 = st1 ? tid / 43 : (tid >> 6);
        const int rstep = st1 ? 5 : 4, nrows = st1 ? 64 : 43, rbytes = st1 ? FS * 2 : DM * 2;
        const float* vec = st1 ? xnT + c * 64 * 4 : hT + (c - 8) * 43 * 4;
        const uint8_t* wb = smem + s * FFN_CHUNK + cg * 16;
        if (!st1 || tid < 43 * 5) {
#pragma unroll 2
            for (int k = r0; k < nrows; k += rstep) {
                const uint4 w = *reinterpret_cast<const uint4*>(wb + k * rbytes);
                const float4 xv = *reinterpret_cast<const float4*>(vec + k * 4);
                const float wf[8] = {bf_lo(w.x), bf_hi(w.x), bf_lo(w.y), bf_hi(w.y), bf_lo(w.z), bf_hi(w.z), bf_lo(w.w), bf_hi(w.w)};
#pragma unroll
                for (int j = 0; j < 8; j++) {
                    acc[0][j] = fmaf(xv.x, wf[j], acc[0][j]);
                    acc[1][j] = fmaf(xv.y, wf[j], acc[1][j]);
                    acc[2][j] = fmaf(xv.z, wf[j], acc[2][j]);
                    acc[3][j] = fmaf(xv.w, wf[j], acc[3][j]);
                }
            }
        }
        __syncthreads();
        if (c + NBF < 16) issue(c + NBF);
        if (c == 7) {
            if (tid < 43 * 5) {
#pragma unroll
                for (int b = 0; b < 4; b++)
#pragma unroll
                    for (int j = 0; j < 8; j++) red[(r0 * 4 + b) * FS + cg * 8 + j] = acc[b][j];
            }
#pragma unroll
            for (int b = 0; b < 4; b++)
#pragma unroll
                for (int j = 0; j < 8; j++) acc[b][j] = 0.f;
            __syncthreads();
            for (int i = tid; i < 4 * FS; i += NTHREADS) {
                const int b = i / FS, cc = i % FS;
                float sum = 0.f;
#pragma unroll
                for (int ks = 0; ks < 5; ks++) sum += red[(ks * 4 + b) * FS + cc];
                hT[cc * 4 + b] = bf16r(silu_f(bf16r(sum)));
            }
            __syncthreads();
        }
    }
    {
        const int cg = tid & 63, fs = tid >> 6;
#pragma unroll
        for (int b = 0; b < 4; b++)
#pragma unroll
            for (int j = 0; j < 8; j++) red[(fs * 4 + b) * DM + cg * 8 + j] = acc[b][j];
    }
    __syncthreads();
    for (int i = tid; i < NB * 256; i += NTHREADS) {
        const int b = i >> 8, j = (i >> 3) & 31, p = i & 7;
        float s0 = 0.f, s1 = 0.f;
#pragma unroll
        for (int fs = 0; fs < 4; fs++) { s0 += red[(fs * 4 + b) * DM + 16 * j + p]; s1 += red[(fs * 4 + b) * DM + 16 * j + 8 + p]; }
        st_relaxed(&g_ffn_part[((b * 32 + j) * N_FFN + f) * 8 + p],
                   make_uint4(__float_as_uint(s0), tag, __float_as_uint(s1), tag));
    }
}

__global__ void __launch_bounds__(NTHREADS, 1)
fused_decode_kernel(const __nv_bfloat16* __restrict__ x, const __nv_bfloat16* __restrict__ Kc,
                    const __nv_bfloat16* __restrict__ Vc, const __nv_bfloat16* __restrict__ wq,
                    const __nv_bfloat16* __restrict__ wo, const __nv_bfloat16* __restrict__ w1,
                    const __nv_bfloat16* __restrict__ w2, __nv_bfloat16* __restrict__ out) {
    extern __shared__ __align__(1024) uint8_t smem[];
    const int cta = blockIdx.x;
    const int tid = threadIdx.x, warp = tid >> 5, lane = tid & 31;
    if (cta >= N_ATT) {
        const uint32_t tag = ld_relaxed32(&g_epoch[cta * 32]);
        ffn_cta(smem, cta - N_ATT, tag, x, w1, w2);
        if (tid < 8) { g_epoch[cta * 32 + tid] = tag + 1; }
        return;
    }

    const int b = cta & 3, h = cta >> 2;
    const int bh = b * NH + h;
    const uint32_t sbase = pin(smem_u32(smem));
    const uint32_t bar_full = sbase + OFF_BAR;
    const uint32_t cnt_rel = bar_full + NST * 8;
    const char* kp = reinterpret_cast<const char*>(Kc) + (size_t)bh * SK * DH * 2;
    const char* vp = reinterpret_cast<const char*>(Vc) + (size_t)bh * SK * DH * 2;
    const char* wop = reinterpret_cast<const char*>(wo) + (size_t)h * DH * DM * 2;
    uint64_t pol;
    asm volatile("createpolicy.fractional.L2::evict_first.b64 %0, 1.0;" : "=l"(pol));
    auto issue_kv = [&](const char* src, int s) {
        const uint32_t bar = bar_full + s * 8;
        mbar_expect_tx(bar, STAGE_BYTES);
        bulk_load(sbase + s * STAGE_BYTES, src, STAGE_BYTES, bar, pol);
    };
    auto issue_first = [&](int n) { issue_kv(((n & 1) ? vp : kp) + (size_t)(n >> 1) * STAGE_BYTES, n); };
    const uint32_t bar_w = bar_full + 216, cnt_w = bar_full + 224;
    auto issue_w = [&](int q) {
        mbar_expect_tx(bar_w, STAGE_BYTES);
        bulk_load_plain(sbase + OFF_W, wop + (size_t)q * STAGE_BYTES, STAGE_BYTES, bar_w);
    };

    const int g = lane >> 2, t = lane & 3;
    float* xn_s  = reinterpret_cast<float*>(smem + OFF_XN);
    float* red_s = reinterpret_cast<float*>(smem + OFF_RED);
    __nv_bfloat16* q_s = reinterpret_cast<__nv_bfloat16*>(smem + OFF_Q);
    float* ml_s = reinterpret_cast<float*>(smem + OFF_ML);
    __nv_bfloat16* o_s = reinterpret_cast<__nv_bfloat16*>(smem + OFF_O);

    uint4* const q_out = &g_q_part[(h * NB + (lane >> 3)) * 32 + b * 8 + (lane & 7)];
    uint4* const a_out = &g_attn_part[((b * 32 + warp * 4 + t) * NH + h) * 8 + g];

    volatile uint32_t* q_flag = reinterpret_cast<volatile uint32_t*>(smem + OFF_BAR + 192);
    const uint32_t bar_x = bar_full + 200;
    if (tid == 0) {
        mbar_init(bar_full, 1);
        issue_first(0);
        mbar_init(bar_x, 1);
        mbar_expect_tx(bar_x, NB * DM * 2);
        bulk_load_plain(sbase + OFF_X, x, NB * DM * 2, bar_x);
#pragma unroll
        for (int s = 1; s < NST; s++) mbar_init(bar_full + s * 8, 1);
        mbar_init(bar_w, 1);
#pragma unroll
        for (int s = 0; s < NST; s++) *reinterpret_cast<volatile uint32_t*>(smem + OFF_BAR + NST * 8 + s * 4) = 0;
        *reinterpret_cast<volatile uint32_t*>(smem + OFF_BAR + 224) = 0;
        *q_flag = 0;
#pragma unroll 1
        for (int s = 1; s < FK_PRE; s++) issue_first(s);
    }
    uint32_t qf[8][2];
    uint32_t tag;
    {
        uint32_t w[32];
        const __nv_bfloat16* wp = wq + (size_t)(warp * 64 + (lane >> 4) * 32) * (NH * DH) + h * DH + b * 32 + (lane & 15) * 2;
#pragma unroll
        for (int i = 0; i < 32; i++) w[i] = ldg_nc32(wp + (size_t)i * (NH * DH));
        tag = ld_relaxed32(&g_epoch[cta * 32]);
        if (tid == 0) {
#pragma unroll 1
            for (int s = FK_PRE; s < FK_FIRST; s++) issue_first(s);
            asm volatile("prefetch.global.L2 [%0];" :: "l"(wop));
        }
        if (warp == 0) st_relaxed(q_out, make_uint4(0, 0, 0, 0));
        __syncthreads();
        if (warp < 4) {
            float xn[16];
            mbar_wait(bar_x, 0);
            const uint4 xa = *reinterpret_cast<const uint4*>(smem + OFF_X + warp * DM * 2 + lane * 32);
            const uint4 xb = *reinterpret_cast<const uint4*>(smem + OFF_X + warp * DM * 2 + lane * 32 + 16);
            warp_layernorm(xa, xb, xn);
#pragma unroll
            for (int i = 0; i < 16; i += 4)
                *reinterpret_cast<float4*>(xn_s + warp * DM + lane * 16 + i) = make_float4(xn[i], xn[i + 1], xn[i + 2], xn[i + 3]);
        }
        __syncthreads();
        float acc[4][2];
#pragma unroll
        for (int bb = 0; bb < 4; bb++) acc[bb][0] = acc[bb][1] = 0.f;
        const float* xp = xn_s + warp * 64 + (lane >> 4) * 32;
#pragma unroll
        for (int i4 = 0; i4 < 8; i4++) {
#pragma unroll
            for (int bb = 0; bb < 4; bb++) {
                const float4 xv = *reinterpret_cast<const float4*>(xp + bb * DM + i4 * 4);
                const float xs[4] = {xv.x, xv.y, xv.z, xv.w};
#pragma unroll
                for (int u = 0; u < 4; u++) {
                    acc[bb][0] = fmaf(xs[u], bf_lo(w[i4 * 4 + u]), acc[bb][0]);
                    acc[bb][1] = fmaf(xs[u], bf_hi(w[i4 * 4 + u]), acc[bb][1]);
                }
            }
        }
        const bool up = lane >= 16;
        float k0 = up ? acc[2][0] : acc[0][0], k1 = up ? acc[2][1] : acc[0][1];
        float k2 = up ? acc[3][0] : acc[1][0], k3 = up ? acc[3][1] : acc[1][1];
        k0 += __shfl_xor_sync(0xffffffffu, up ? acc[0][0] : acc[2][0], 16);
        k1 += __shfl_xor_sync(0xffffffffu, up ? acc[0][1] : acc[2][1], 16);
        k2 += __shfl_xor_sync(0xffffffffu, up ? acc[1][0] : acc[3][0], 16);
        k3 += __shfl_xor_sync(0xffffffffu, up ? acc[1][1] : acc[3][1], 16);
        float* rp = red_s + warp * 128 + (up ? 64 : 0) + (lane & 15) * 2;
        *reinterpret_cast<float2*>(rp)      = make_float2(k0, k1);
        *reinterpret_cast<float2*>(rp + 32) = make_float2(k2, k3);
        __syncthreads();
        if (warp == 0) {
            float4 s = make_float4(0.f, 0.f, 0.f, 0.f);
#pragma unroll
            for (int w8 = 0; w8 < NCW; w8++) {
                const float4 v = *reinterpret_cast<const float4*>(red_s + w8 * 128 + lane * 4);
                s.x += v.x; s.y += v.y; s.z += v.z; s.w += v.w;
            }
            st_relaxed(q_out, make_uint4(pack_bf16(s.x, s.y), tag, pack_bf16(s.z, s.w), tag));
            const uint4* p = &g_q_part[(h * NB + b) * 32 + lane];
            uint4 v = ld_relaxed(p);
            for (int spin = 0; !ll_valid(v, tag) && spin < (1 << 20); spin++) v = ld_relaxed(p);
            *reinterpret_cast<uint2*>(q_s + lane * 4) = make_uint2(v.x, v.z);
            if (lane == 0) *q_flag = 1;
        }
        if (tid == NTHREADS - 32) {
            int next = FK_FIRST, watch = 0;
            while (next < NST) {
                if (mbar_test(bar_full + watch * 8, 0)) { issue_first(next); next++; watch++; }
                else if (*q_flag) break;
            }
#pragma unroll 1
            for (; next < NST; next++) issue_first(next);
        }
        __syncthreads();
#pragma unroll
        for (int j = 0; j < 8; j++) {
            const int c = (j ^ g) & 7;
            qf[j][0] = *reinterpret_cast<const uint32_t*>(q_s + c * 8 + 2 * t);
            qf[j][1] = *reinterpret_cast<const uint32_t*>(q_s + 64 + c * 8 + 2 * t);
        }
    }

    constexpr float RSQRT_DH = 0.08838834764831845f, LOG2E = 1.4426950408889634f;
    const int li = lane & 7, lm = lane >> 3;
    const uint32_t k_base = pin(sbase + (uint32_t)((warp * 16 + li + 8 * (lm & 1)) * 256 + (lm >> 1) * 128 + li * 16));
    const uint32_t v_base = pin(sbase + (uint32_t)((warp * 16 + li + 8 * (lm >> 1)) * 256 + (lm & 1) * 128 + li * 16));
    const bool diag = (t == (g >> 1));
    uint32_t msk[8];
#pragma unroll
    for (int j = 0; j < 8; j++) msk[j] = pin((j == (g ^ (2 * t)) ? 0x0000ffffu : 0u) | (j == (g ^ (2 * t) ^ 1) ? 0xffff0000u : 0u));
    const uint32_t ones[4] = {0x3f803f80u, 0x3f803f80u, 0x3f803f80u, 0x3f803f80u};

    float acc0[4] = {0.f, 0.f, 0.f, 0.f}, acc1[4] = {0.f, 0.f, 0.f, 0.f}, lacc[4] = {0.f, 0.f, 0.f, 0.f};
    float m_raw = -INFINITY;
    float m_run = -INFINITY, mc = 0.f;
    float fin_scale = 0.f;
    int st = 0; uint32_t ph = 0;
    int seq = NST;
    uint32_t wa[8][4][4];
    float g0 = 0.f, g1 = 0.f;
    uint4 gv = make_uint4(0, 0, 0, 0);
    const int cp = lane & 7, q4 = lane >> 3;
    const float x0 = __bfloat162float(reinterpret_cast<const __nv_bfloat16*>(smem + OFF_X)[b * DM + h * 16 + cp]);
    const float x1 = __bfloat162float(reinterpret_cast<const __nv_bfloat16*>(smem + OFF_X)[b * DM + h * 16 + 8 + cp]);
    const uint32_t prog_base = (tag - 1) * (uint32_t)(N_ATT * NT);
    const uint32_t prog_s = bar_full + 208;
    uint32_t prog_v = prog_base;
    if (tid == 0) *reinterpret_cast<volatile uint32_t*>(smem + OFF_BAR + 208) = prog_base;
    __syncthreads();
    auto pace = [&](uint32_t pv, uint32_t lim) {
        for (int spin = 0; (int)(pv - lim) < 0 && spin < 4096; spin++) pv = ld_relaxed32(&g_progress[0]);
    };

#pragma unroll 1
    for (int it = 0; it < NT; it++) {
#pragma unroll
        for (int q = 0; q <= 4; q++) {
            if (it == FK_WTILE + q * FK_WSTEP) {
                if (q == 0) {
                    if (tid == 0) {
                        asm volatile("fence.proxy.async.shared::cta;" ::: "memory");
                        issue_w(0);
                    }
                } else {
                    mbar_wait(bar_w, (q - 1) & 1);
                    const uint32_t wb = sbase + OFF_W + (li + 8 * (lane >> 4)) * 1024 + warp * 128 + (lm & 1) * 16;
#pragma unroll
                    for (int j = 0; j < 4; j++) {
                        ldsm_x4_t(wa[2 * q - 2][j], wb + j * 32);
                        ldsm_x4_t(wa[2 * q - 1][j], wb + 16384 + j * 32);
                    }
                    if (q < 4 && lane == 0) {
                        const uint32_t rel = atom_inc_shared(cnt_w);
                        if ((rel & (NCW - 1)) == NCW - 1) issue_w(q);
                    }
                }
                __syncwarp();
            }
        }
        if (it == 2 && tid < 8) g_epoch[cta * 32 + tid] = tag + 1;
        if (it == FK_INIT_AT) st_relaxed(a_out, make_uint4(0, 0, 0, 0));
        if (it == NT - 14 && warp == 0) {
            gv = ld_relaxed(&g_ffn_part[((b * 32 + h) * N_FFN + q4) * 8 + cp]);
        }
        if (it == NT - 6 && warp == 0) {
            const uint4* p = &g_ffn_part[((b * 32 + h) * N_FFN + q4) * 8 + cp];
            uint4 v = gv;
            for (int spin = 0; !ll_valid(v, tag) && spin < (1 << 20); spin++) { __nanosleep(64); v = ld_relaxed(p); }
            __syncwarp();
            g0 = __uint_as_float(v.x); g1 = __uint_as_float(v.z);
            g0 += __shfl_xor_sync(0xffffffffu, g0, 8);  g1 += __shfl_xor_sync(0xffffffffu, g1, 8);
            g0 += __shfl_xor_sync(0xffffffffu, g0, 16); g1 += __shfl_xor_sync(0xffffffffu, g1, 16);
            g0 = bf16r(silu_f(bf16r(g0))); g1 = bf16r(silu_f(bf16r(g1)));
        }
        if (tid == 0) {
            *reinterpret_cast<volatile uint32_t*>(smem + OFF_BAR + 208) = prog_v;
            prog_v = ld_relaxed32(&g_progress[0]);
        }
        const bool endgame = it >= NT - FK_ENDT;
        const char* k_next = kp + (size_t)(it + NST / 2) * STAGE_BYTES;
        const char* v_next = vp + (size_t)(it + NST / 2) * STAGE_BYTES;
        mbar_wait(bar_full + st * 8, ph);
        float c0[4] = {0.f, 0.f, 0.f, 0.f}, c1[4] = {0.f, 0.f, 0.f, 0.f};
        uint32_t relK = 0, pvK = 0;
        const uint32_t kb = k_base + st * STAGE_BYTES;
        {
#pragma unroll
            for (int j = 0; j < 8; j++) {
                uint32_t a[4];
                ldsm_x4(a, kb ^ (j << 4));
                mma_bf16((j & 1) ? c1 : c0, a, qf[j][0], qf[j][1]);
            }
            if (!endgame && seq < NSEQ && lane == 0) {
                relK = atom_inc_shared(cnt_rel + st * 4);
                pvK = lds32(prog_s);
            }
        }
        const float u0 = (g & 1) ? (c0[1] + c1[1]) : (c0[0] + c1[0]);
        const float u1 = (g & 1) ? (c0[3] + c1[3]) : (c0[2] + c1[2]);
        int key = __float_as_int(diag ? fmaxf(u0, u1) : -INFINITY);
        key ^= (key >> 31) & 0x7fffffff;
        key = __reduce_max_sync(0xffffffffu, key);
        const uint32_t r1 = pack_bf16(u0, u1);
        const uint32_t r2 = pack_bf16(bf_lo(r1) * RSQRT_DH, bf_hi(r1) * RSQRT_DH);
        const float s0 = diag ? bf_lo(r2) : -INFINITY, s1 = diag ? bf_hi(r2) : -INFINITY;
        key ^= (key >> 31) & 0x7fffffff;
        const float tmax = __int_as_float(key);
        if (tmax > m_raw) {
            m_raw = tmax;
            const float m_new = bf16r(bf16r(tmax) * RSQRT_DH);
            const float sc = ex2((m_run - m_new) * LOG2E);
#pragma unroll
            for (int i = 0; i < 4; i++) { acc0[i] *= sc; acc1[i] *= sc; }
            lacc[0] *= sc;
            m_run = m_new;
            mc = -m_new * LOG2E;
        }
        const uint32_t pk = pack_bf16(ex2(fmaf(s0, LOG2E, mc)), ex2(fmaf(s1, LOG2E, mc)));
        const uint32_t xx = __shfl_sync(0xffffffffu, pk, 9 * t), yy = __shfl_sync(0xffffffffu, pk, 9 * t + 4);
        const uint32_t pp0 = __byte_perm(xx, yy, 0x5410), pp1 = __byte_perm(xx, yy, 0x7632);
        if ((relK & (NCW - 1)) == NCW - 1) {
            pace(pvK, prog_base + (uint32_t)(it * N_ATT - (FK_LEAD)));
            issue_kv(k_next, st);
        }
        __syncwarp();
        const int stK = st;
        seq++;
        if (++st == NST) { st = 0; ph ^= 1; }
        mma_bf16(lacc, ones, pp0, pp1);
        if (it == NT - 1) {
            if (lane == 0) { ml_s[warp] = m_run; ml_s[8 + warp] = lacc[0]; }
            __syncthreads();
            const float4 ma = *reinterpret_cast<const float4*>(ml_s), mb = *reinterpret_cast<const float4*>(ml_s + 4);
            const float4 la = *reinterpret_cast<const float4*>(ml_s + 8), lb = *reinterpret_cast<const float4*>(ml_s + 12);
            const float M = fmaxf(fmaxf(fmaxf(ma.x, ma.y), fmaxf(ma.z, ma.w)), fmaxf(fmaxf(mb.x, mb.y), fmaxf(mb.z, mb.w)));
            const float L = (ex2((ma.x - M) * LOG2E) * la.x + ex2((ma.y - M) * LOG2E) * la.y) + (ex2((ma.z - M) * LOG2E) * la.z + ex2((ma.w - M) * LOG2E) * la.w)
                          + (ex2((mb.x - M) * LOG2E) * lb.x + ex2((mb.y - M) * LOG2E) * lb.y) + (ex2((mb.z - M) * LOG2E) * lb.z + ex2((mb.w - M) * LOG2E) * lb.w);
            fin_scale = __fdividef(ex2((m_run - M) * LOG2E), L);
        }
        mbar_wait(bar_full + st * 8, ph);
        const uint32_t vb = v_base + st * STAGE_BYTES;
        {
            uint32_t relV = 0, pvV = 0;
#pragma unroll
            for (int j = 0; j < 8; j++) {
                uint32_t a[4];
                ldsm_x4_t(a, vb ^ (j << 4));
                mma_bf16((j & 1) ? acc1 : acc0, a, pp0 & msk[j], pp1 & msk[j]);
            }
            if (seq - (endgame ? 1 : 0) < NSEQ && lane == 0) {
                relV = atom_inc_shared(cnt_rel + st * 4);
                pvV = lds32(prog_s);
            }
            if (tid == NTHREADS - 32) asm volatile("red.relaxed.gpu.global.add.u32 [%0], 1;" :: "l"(&g_progress[0]) : "memory");
            if ((relV & (NCW - 1)) == NCW - 1) {
                if (endgame) {
                    pace(pvV, prog_base + (uint32_t)((it + 1) * N_ATT - (FK_LEAD_END)));
                    issue_kv(k_next, stK);
                }
                if (seq < NSEQ) issue_kv(v_next, st);
            }
        }
        __syncwarp();
        seq++;
        if (++st == NST) { st = 0; ph ^= 1; }
    }

    if ((prog_v ^ gv.x ^ gv.y ^ gv.z ^ gv.w) == 0x9e3779b9u) *reinterpret_cast<volatile uint32_t*>(smem + OFF_BAR + 240) = 0;
    const uint4* inbox = &g_attn_part[((b * 32 + h) * NH + q4 * 8) * 8 + cp];
    asm volatile("" : "+l"(inbox));
    {
        float* o = red_s + warp * 128;
        o[16 * t + g]          = (acc0[0] + acc1[0]) * fin_scale;
        o[16 * t + 8 + g]      = (acc0[1] + acc1[1]) * fin_scale;
        o[64 + 16 * t + g]     = (acc0[2] + acc1[2]) * fin_scale;
        o[64 + 16 * t + 8 + g] = (acc0[3] + acc1[3]) * fin_scale;
    }
    __syncthreads();
    if (tid < DH) {
        float v[8];
#pragma unroll
        for (int w = 0; w < 8; w++) v[w] = red_s[w * 128 + tid];
        const float o = ((v[0] + v[1]) + (v[2] + v[3])) + ((v[4] + v[5]) + (v[6] + v[7]));
        o_s[((tid >> 1) & 3) * 32 + (tid >> 4) * 4 + ((tid >> 3) & 1) * 2 + (tid & 1)] = __float2bfloat16_rn(o);
    }
    __syncthreads();
    {
        float d[4][4];
#pragma unroll
        for (int j = 0; j < 4; j++) { d[j][0] = d[j][1] = d[j][2] = d[j][3] = 0.f; }
        uint4 ov[4];
#pragma unroll
        for (int i = 0; i < 4; i++) ov[i] = *reinterpret_cast<const uint4*>(o_s + t * 32 + i * 8);
#pragma unroll
        for (int i = 0; i < 4; i++) {
#pragma unroll
            for (int j = 0; j < 4; j++) mma_bf16(d[j], wa[2 * i][j], ov[i].x, ov[i].y);
#pragma unroll
            for (int j = 0; j < 4; j++) mma_bf16(d[j], wa[2 * i + 1][j], ov[i].z, ov[i].w);
        }
        float r0 = d[0][0], r1 = d[0][2];
        if (t == 1) { r0 = d[1][0]; r1 = d[1][2]; }
        if (t == 2) { r0 = d[2][0]; r1 = d[2][2]; }
        if (t == 3) { r0 = d[3][0]; r1 = d[3][2]; }
        st_relaxed(a_out, make_uint4(__float_as_uint(r0), tag, __float_as_uint(r1), tag));
    }
    if (warp == 0) {
        const uint4* p = inbox;
        uint4 v[8];
#pragma unroll
        for (int i = 0; i < 8; i++) v[i] = ld_relaxed(p + i * 8);
#pragma unroll 1
        for (int spin = 0; spin < (1 << 20); spin++) {
            uint32_t bad[8];
#pragma unroll
            for (int i = 0; i < 8; i++) bad[i] = (v[i].y ^ tag) | (v[i].w ^ tag);
            if ((((bad[0] | bad[1]) | (bad[2] | bad[3])) | ((bad[4] | bad[5]) | (bad[6] | bad[7]))) == 0) break;
#pragma unroll
            for (int i = 0; i < 8; i++) {
                if (bad[i] != 0) v[i] = ld_relaxed(p + i * 8);
            }
        }
        __syncwarp();
        float s0 = ((__uint_as_float(v[0].x) + __uint_as_float(v[1].x)) + (__uint_as_float(v[2].x) + __uint_as_float(v[3].x)))
                 + ((__uint_as_float(v[4].x) + __uint_as_float(v[5].x)) + (__uint_as_float(v[6].x) + __uint_as_float(v[7].x)));
        float s1 = ((__uint_as_float(v[0].z) + __uint_as_float(v[1].z)) + (__uint_as_float(v[2].z) + __uint_as_float(v[3].z)))
                 + ((__uint_as_float(v[4].z) + __uint_as_float(v[5].z)) + (__uint_as_float(v[6].z) + __uint_as_float(v[7].z)));
        s0 += __shfl_xor_sync(0xffffffffu, s0, 8);  s1 += __shfl_xor_sync(0xffffffffu, s1, 8);
        s0 += __shfl_xor_sync(0xffffffffu, s0, 16); s1 += __shfl_xor_sync(0xffffffffu, s1, 16);
        const uint32_t sb = pack_bf16(s0, s1);
        const uint32_t sg = pack_bf16(bf_lo(sb) * g0, bf_hi(sb) * g1);
        const uint32_t ob = pack_bf16(x0 + bf_lo(sg), x1 + bf_hi(sg));
        const int src = (2 * lane) & 7;
        const uint32_t e0 = __shfl_sync(0xffffffffu, ob, src), e1 = __shfl_sync(0xffffffffu, ob, src + 1);
        if (lane < 8)
            *reinterpret_cast<uint32_t*>(out + b * DM + h * 16 + 2 * lane) = __byte_perm(e0, e1, lane < 4 ? 0x5410 : 0x7632);
    }
}

}

extern "C" void kernel_launch(void* const* d_in, const int* in_sizes, int n_in, void* d_out, int out_size) {
    (void)in_sizes; (void)n_in; (void)out_size;
    const __nv_bfloat16* x  = (const __nv_bfloat16*)d_in[0];
    const __nv_bfloat16* Kc = (const __nv_bfloat16*)d_in[1];
    const __nv_bfloat16* Vc = (const __nv_bfloat16*)d_in[2];
    const __nv_bfloat16* wq = (const __nv_bfloat16*)d_in[3];
    const __nv_bfloat16* wo = (const __nv_bfloat16*)d_in[4];
    const __nv_bfloat16* w1 = (const __nv_bfloat16*)d_in[6];
    const __nv_bfloat16* w2 = (const __nv_bfloat16*)d_in[7];

    static bool attr_set = false;
    if (!attr_set) {
        cudaFuncSetAttribute(fk::fused_decode_kernel, cudaFuncAttributeMaxDynamicSharedMemorySize, fk::SMEM_BYTES);
        attr_set = true;
    }
    fk::fused_decode_kernel<<<fk::N_CTA, fk::NTHREADS, fk::SMEM_BYTES>>>(x, Kc, Vc, wq, wo, w1, w2, (__nv_bfloat16*)d_out);
}
```
